```python
import torch

def _softmax(x, axis=-1):
    return torch.softmax(x, dim=axis)
def _gelu(x):
    return torch.nn.functional.gelu(x, approximate="tanh")
def _silu(x):
    return torch.nn.functional.silu(x)
def _sigmoid(x):
    return torch.sigmoid(x)
def _layernorm(x, axis=-1, eps=1e-5):
    m = x.mean(dim=axis, keepdim=True)
    v = x.var(dim=axis, keepdim=True, unbiased=False)
    return (x - m) / torch.sqrt(v + eps)
def _scatter_add(tgt, idx, src, axis=0):
    return tgt.clone().index_add_(axis, idx, src)
def _segment_sum(src, seg, n):
    out = torch.zeros((n,) + src.shape[1:], dtype=src.dtype)
    return out.index_add_(0, seg, src)
def _pad(x, pw):
    flat = tuple(v for pair in reversed(pw) for v in pair)
    return torch.nn.functional.pad(x, flat)

kernel_name = 'concat_heads__linear_kernel_hedgehog__ssm_conv_s5__prompt'

def setup_inputs():

    _w = (lambda a: (lambda t: t.to(torch.bfloat16) if t.is_floating_point() else t)(torch.as_tensor(a)))
    def _A_setup():
        B, S, D, H = 1, 2048, 1024, 32
        Dh = D // H
        return {
            "x": _w((lambda *s: torch.randn(*s, dtype=torch.bfloat16) * 0.4)(B, S, D)),
            "wqkv": _w((lambda *s: torch.randn(*s, dtype=torch.bfloat16) * 0.4)(D, 3 * D)),
            "w_phi": _w((lambda *s: torch.randn(*s, dtype=torch.bfloat16) * 0.4)(H, Dh, Dh) * (Dh ** -0.5)),
            "wo": _w((lambda *s: torch.randn(*s, dtype=torch.bfloat16) * 0.05)(D, D)),
        }
    _A_in = _A_setup()

    def _B_setup():
        B, S, D = 1, 2048, 1024
        P = D
        Lambda_re = -0.5 * (lambda _x: torch.exp(torch.as_tensor(_x)))((lambda *s: torch.randn(*s, dtype=torch.bfloat16) * 0.8)(P))
        Lambda_im = (lambda *s: torch.randn(*s, dtype=torch.bfloat16) * 0.8)(P) * 1.0
        B_re = (lambda *s: torch.randn(*s, dtype=torch.bfloat16) * 0.8)(P, D) * (D ** -0.5)
        B_im = (lambda *s: torch.randn(*s, dtype=torch.bfloat16) * 0.8)(P, D) * (D ** -0.5)
        C_re = (lambda *s: torch.randn(*s, dtype=torch.bfloat16) * 0.8)(D, P) * (P ** -0.5)
        C_im = (lambda *s: torch.randn(*s, dtype=torch.bfloat16) * 0.8)(D, P) * (P ** -0.5)
        log_dt = (lambda *s: torch.randn(*s, dtype=torch.bfloat16) * 0.8)(P) * 0.3 - 2.0
        Dskip = (lambda *s: torch.randn(*s, dtype=torch.bfloat16) * 0.8)(D)
        return {
            "x": _w((lambda *s: torch.randn(*s, dtype=torch.bfloat16) * 0.05)(B, S, D)),
            "Lambda_re": _w(Lambda_re),
            "Lambda_im": _w(Lambda_im),
            "B_re": _w(B_re),
            "B_im": _w(B_im),
            "C_re": _w(C_re),
            "C_im": _w(C_im),
            "log_dt": _w(log_dt),
            "Dskip": _w(Dskip),
        }
    _B_in = _B_setup()

    return {
        "A_x": _A_in["x"],
        "A_wqkv": _A_in["wqkv"],
        "A_w_phi": _A_in["w_phi"],
        "A_wo": _A_in["wo"],
        "B_x": _B_in["x"],
        "B_Lambda_re": _B_in["Lambda_re"],
        "B_Lambda_im": _B_in["Lambda_im"],
        "B_B_re": _B_in["B_re"],
        "B_B_im": _B_in["B_im"],
        "B_C_re": _B_in["C_re"],
        "B_C_im": _B_in["C_im"],
        "B_log_dt": _B_in["log_dt"],
        "B_Dskip": _B_in["Dskip"],
    }

def reference(A_x, A_wqkv, A_w_phi, A_wo, B_x, B_Lambda_re, B_Lambda_im, B_B_re, B_B_im, B_C_re, B_C_im, B_log_dt, B_Dskip):
    def _A_ref(x, wqkv, w_phi, wo):
        B, S, D = x.shape
        H = 32; Dh = D // H
        qkv = (lambda x, *d: x.permute(*d))((x @ wqkv).reshape(B, S, 3, H, Dh), 2, 0, 3, 1, 4)
        q, k, v = qkv[0], qkv[1], qkv[2]
        pq = torch.einsum("bhsd,hdf->bhsf", q, w_phi)
        pk = torch.einsum("bhsd,hdf->bhsf", k, w_phi)
        phi_q = torch.concatenate([_softmax(pq, axis=-1), _softmax(-pq, axis=-1)], axis=-1)
        phi_k = torch.concatenate([_softmax(pk, axis=-1), _softmax(-pk, axis=-1)], axis=-1)
        kv = torch.einsum("bhsf,bhsd->bhfd", phi_k, v)
        z  = torch.einsum("bhsf->bhf", phi_k)
        num = torch.einsum("bhqf,bhfd->bhqd", phi_q, kv)
        den = torch.einsum("bhqf,bhf->bhq", phi_q, z)[..., None] + 1e-6
        o = num / den
        return (lambda x, *d: x.permute(*d))(o, 0, 2, 1, 3).reshape(B, S, D) @ wo

    def _B_ref(x, Lambda_re, Lambda_im, B_re, B_im, C_re, C_im, log_dt, Dskip):
        Bsz, L, H = x.shape
        Lam = Lambda_re + 1j * Lambda_im
        Bmat = B_re + 1j * B_im
        Cmat = C_re + 1j * C_im
        dt = torch.exp(log_dt)
        Lam_bar = torch.exp(dt * Lam)
        B_bar = ((Lam_bar - 1.0) / Lam)[:, None] * Bmat
        Bu = torch.einsum("bld,pd->blp", x + 0j, B_bar)
        h = torch.zeros_like(Bu[:, 0, :])
        hs = []
        for t in range(L):
            h = Lam_bar[None, :] * h + Bu[:, t, :]
            hs.append(h)
        hseq = torch.stack(hs, 1)
        y = 2.0 * torch.einsum("blp,dp->bld", hseq, Cmat).real + x * Dskip[None, None, :]
        return y

    a = _A_ref(A_x, A_wqkv, A_w_phi, A_wo)
    b = _B_ref(B_x, B_Lambda_re, B_Lambda_im, B_B_re, B_B_im, B_C_re, B_C_im, B_log_dt, B_Dskip)
    return torch.concatenate([a, b], axis=-1)
```

```cpp
#include <cuda_runtime.h>
#include <cuda_bf16.h>
#include <cuda.h>
#include <stdint.h>

namespace {

constexpr int NCTA = 128;
constexpr int NTHREADS = 640;
constexpr int REG_MMA = 160, REG_EPI = 64, REG_PROD = 32;
constexpr int STAGES = 3;
constexpr int STAGE_BYTES = 49152;
constexpr int SM_STG = STAGES * STAGE_BYTES;
constexpr int SM_P = SM_STG + 65536;
constexpr int SM_ONES = SM_P + 16384;
constexpr int SM_BAR = SM_ONES + 256;
constexpr int SMEM_BYTES = SM_BAR + 256;
constexpr float LOG2E = 1.4426950408889634f;
constexpr uint32_t SPIN_LIMIT = 1u << 26;

struct Params {
  CUtensorMap mBre, mBim, mBxB, mAx, mWf, mWv, mHT, mCre, mCim, mO, mWo, mOut, mBxT;
  const __nv_bfloat16 *wqkv, *wphi, *lam_re, *lam_im, *log_dt, *dskip;
  const __nv_bfloat16 *ax, *cre, *cim, *wo;
};

__device__ __nv_bfloat16 g_Wf[1024 * 2048];
__device__ __nv_bfloat16 g_hT[2048 * 2048];
__device__ __nv_bfloat16 g_o[2048 * 1024];
__device__ float g_kv[32 * 64 * 32];
__device__ float g_z[32 * 64];
__device__ ulonglong2 g_agg[16 * 8 * 64];
__device__ uint32_t g_epoch[NCTA];
__device__ uint32_t g_cnt_setup;
__device__ uint32_t g_cnt_h[8];
__device__ uint32_t g_cnt_kv[8];
__device__ uint32_t g_cnt_o[64];

__device__ __forceinline__ uint32_t smem_u32(const void* p) { return (uint32_t)__cvta_generic_to_shared(p); }
__device__ __forceinline__ void mbar_init(uint32_t bar, uint32_t count) {
  asm volatile("mbarrier.init.shared::cta.b64 [%0], %1;" :: "r"(bar), "r"(count) : "memory");
}
__device__ __forceinline__ void mbar_expect_tx(uint32_t bar, uint32_t bytes) {
  asm volatile("mbarrier.arrive.expect_tx.shared::cta.b64 _, [%0], %1;" :: "r"(bar), "r"(bytes) : "memory");
}
__device__ __forceinline__ void mbar_arrive(uint32_t bar) {
  asm volatile("mbarrier.arrive.shared::cta.b64 _, [%0];" :: "r"(bar) : "memory");
}
__device__ __forceinline__ bool mbar_try_wait(uint32_t bar, uint32_t parity) {
  uint32_t ok;
  asm volatile("{\n.reg .pred p;\nmbarrier.try_wait.parity.shared::cta.b64 p, [%1], %2;\nselp.u32 %0, 1, 0, p;\n}"
               : "=r"(ok) : "r"(bar), "r"(parity) : "memory");
  return ok;
}
__device__ __forceinline__ void mbar_wait(uint32_t bar, uint32_t parity) {
  uint32_t n = 0;
  while (!mbar_try_wait(bar, parity)) { if (++n > SPIN_LIMIT) __trap(); }
}
__device__ __forceinline__ void fence_async_smem() { asm volatile("fence.proxy.async.shared::cta;" ::: "memory"); }
__device__ __forceinline__ void fence_async_all() { asm volatile("fence.proxy.async;" ::: "memory"); }
__device__ __forceinline__ void bar_sync(int id, int n) { asm volatile("bar.sync %0, %1;" :: "r"(id), "r"(n) : "memory"); }

__device__ __forceinline__ void tma_load(uint32_t dst, const CUtensorMap* map, int c0, int c1, uint32_t bar) {
  asm volatile("cp.async.bulk.tensor.2d.shared::cluster.global.mbarrier::complete_tx::bytes [%0], [%1, {%3, %4}], [%2];"
               :: "r"(dst), "l"(map), "r"(bar), "r"(c0), "r"(c1) : "memory");
}
__device__ __forceinline__ void tma_store(const CUtensorMap* map, uint32_t src, int c0, int c1) {
  asm volatile("cp.async.bulk.tensor.2d.global.shared::cta.bulk_group [%0, {%2, %3}], [%1];"
               :: "l"(map), "r"(src), "r"(c0), "r"(c1) : "memory");
}
__device__ __forceinline__ void bulk_commit() { asm volatile("cp.async.bulk.commit_group;" ::: "memory"); }
__device__ __forceinline__ void bulk_wait_all() { asm volatile("cp.async.bulk.wait_group 0;" ::: "memory"); }
__device__ __forceinline__ void prefetch_map(const CUtensorMap* map) {
  asm volatile("prefetch.tensormap [%0];" :: "l"(map) : "memory");
}
__device__ __forceinline__ void prefetch_l2(const void* p, uint32_t bytes) {
  asm volatile("cp.async.bulk.prefetch.L2.global [%0], %1;" :: "l"(p), "r"(bytes) : "memory");
}
__device__ __forceinline__ void wgmma_fence() { asm volatile("wgmma.fence.sync.aligned;" ::: "memory"); }
__device__ __forceinline__ void wgmma_commit() { asm volatile("wgmma.commit_group.sync.aligned;" ::: "memory"); }
template <int N> __device__ __forceinline__ void wgmma_wait() { asm volatile("wgmma.wait_group.sync.aligned %0;" :: "n"(N) : "memory"); }
template <int R> __device__ __forceinline__ void fence_regs(float (&d)[R]) {
#pragma unroll
  for (int i = 0; i < R; i++) asm volatile("" : "+f"(d[i]) :: "memory");
}
__host__ __device__ constexpr uint64_t desc_base(uint32_t lbo, uint32_t sbo, uint32_t swz) {
  return ((uint64_t)((lbo & 0x3FFFF) >> 4) << 16) | ((uint64_t)((sbo & 0x3FFFF) >> 4) << 32) | ((uint64_t)swz << 62);
}
__device__ __forceinline__ uint64_t make_desc(uint32_t addr, uint64_t base) { return base | (uint64_t)((addr & 0x3FFFF) >> 4); }
template <int R> __device__ __forceinline__ void reg_alloc() { asm volatile("setmaxnreg.inc.sync.aligned.u32 %0;" :: "n"(R)); }
template <int R> __device__ __forceinline__ void reg_dealloc() { asm volatile("setmaxnreg.dec.sync.aligned.u32 %0;" :: "n"(R)); }

__device__ __forceinline__ void ldsm4(uint32_t addr, uint32_t& r0, uint32_t& r1, uint32_t& r2, uint32_t& r3) {
  asm volatile("ldmatrix.sync.aligned.m8n8.x4.shared.b16 {%0, %1, %2, %3}, [%4];"
               : "=r"(r0), "=r"(r1), "=r"(r2), "=r"(r3) : "r"(addr) : "memory");
}
__device__ __forceinline__ void stsm4(uint32_t addr, uint32_t r0, uint32_t r1, uint32_t r2, uint32_t r3) {
  asm volatile("stmatrix.sync.aligned.m8n8.x4.shared.b16 [%0], {%1, %2, %3, %4};"
               :: "r"(addr), "r"(r0), "r"(r1), "r"(r2), "r"(r3) : "memory");
}
__device__ __forceinline__ uint4 lds128(uint32_t addr) {
  uint4 v;
  asm volatile("ld.shared.v4.u32 {%0, %1, %2, %3}, [%4];" : "=r"(v.x), "=r"(v.y), "=r"(v.z), "=r"(v.w) : "r"(addr) : "memory");
  return v;
}
__device__ __forceinline__ void sts128(uint32_t addr, uint4 v) {
  asm volatile("st.shared.v4.u32 [%0], {%1, %2, %3, %4};" :: "r"(addr), "r"(v.x), "r"(v.y), "r"(v.z), "r"(v.w) : "memory");
}
__device__ __forceinline__ uint32_t lds32(uint32_t addr) {
  uint32_t v; asm volatile("ld.shared.u32 %0, [%1];" : "=r"(v) : "r"(addr) : "memory"); return v;
}
__device__ __forceinline__ float2 lds64f(uint32_t addr) {
  float2 v; asm volatile("ld.shared.v2.f32 {%0, %1}, [%2];" : "=f"(v.x), "=f"(v.y) : "r"(addr) : "memory"); return v;
}
__device__ __forceinline__ void sts64f(uint32_t addr, float a, float b) {
  asm volatile("st.shared.v2.f32 [%0], {%1, %2};" :: "r"(addr), "f"(a), "f"(b) : "memory");
}
__device__ __forceinline__ uint32_t pack_bf16(float lo, float hi) {
  uint32_t r; asm("cvt.rn.bf16x2.f32 %0, %1, %2;" : "=r"(r) : "f"(hi), "f"(lo)); return r;
}
__device__ __forceinline__ float bf_lo(uint32_t v) { return __uint_as_float(v << 16); }
__device__ __forceinline__ float bf_hi(uint32_t v) { return __uint_as_float(v & 0xffff0000u); }
__device__ __forceinline__ float ex2(float x) { float y; asm("ex2.approx.ftz.f32 %0, %1;" : "=f"(y) : "f"(x)); return y; }
__device__ __forceinline__ float rcp(float x) { float y; asm("rcp.approx.ftz.f32 %0, %1;" : "=f"(y) : "f"(x)); return y; }
__device__ __forceinline__ uint32_t hmax2(uint32_t a, uint32_t b) { uint32_t r; asm("max.bf16x2 %0, %1, %2;" : "=r"(r) : "r"(a), "r"(b)); return r; }
__device__ __forceinline__ uint32_t hmin2(uint32_t a, uint32_t b) { uint32_t r; asm("min.bf16x2 %0, %1, %2;" : "=r"(r) : "r"(a), "r"(b)); return r; }
__device__ __forceinline__ void mma16816(float (&c)[4], uint32_t a0, uint32_t a1, uint32_t a2, uint32_t a3, uint32_t b0, uint32_t b1) {
  asm volatile("mma.sync.aligned.m16n8k16.row.col.f32.bf16.bf16.f32 {%0, %1, %2, %3}, {%4, %5, %6, %7}, {%8, %9}, {%0, %1, %2, %3};"
               : "+f"(c[0]), "+f"(c[1]), "+f"(c[2]), "+f"(c[3]) : "r"(a0), "r"(a1), "r"(a2), "r"(a3), "r"(b0), "r"(b1));
}
__device__ __forceinline__ uint32_t ld_acquire(const uint32_t* p) {
  uint32_t v; asm volatile("ld.acquire.gpu.global.u32 %0, [%1];" : "=r"(v) : "l"(p) : "memory"); return v;
}
__device__ __forceinline__ void red_release_add(uint32_t* p, uint32_t v) {
  asm volatile("red.release.gpu.global.add.u32 [%0], %1;" :: "l"(p), "r"(v) : "memory");
}
__device__ __forceinline__ void wait_counter(const uint32_t* p, uint32_t target) {
  uint32_t n = 0;
  while ((int32_t)(ld_acquire(p) - target) < 0) { __nanosleep(32); if (++n > (SPIN_LIMIT >> 4)) __trap(); }
}
__device__ __forceinline__ void red_add_v2(float* p, float a, float b) {
  asm volatile("red.global.add.v2.f32 [%0], {%1, %2};" :: "l"(p), "f"(a), "f"(b) : "memory");
}

__device__ __forceinline__ void wgmma_n128_kk(float (&d)[64], uint64_t descA, uint64_t descB, int scaleD) {
  asm volatile(
    "{\n.reg .pred p;\nsetp.ne.b32 p, %66, 0;\n"
    "wgmma.mma_async.sync.aligned.m64n128k16.f32.bf16.bf16 "
    "{%0, %1, %2, %3, %4, %5, %6, %7, %8, %9, %10, %11, %12, %13, %14, %15, "
    "%16, %17, %18, %19, %20, %21, %22, %23, %24, %25, %26, %27, %28, %29, %30, %31, "
    "%32, %33, %34, %35, %36, %37, %38, %39, %40, %41, %42, %43, %44, %45, %46, %47, "
    "%48, %49, %50, %51, %52, %53, %54, %55, %56, %57, %58, %59, %60, %61, %62, %63}, "
    "%64, %65, p, 1, 1, 0, 0;\n}\n"
    : "+f"(d[0]), "+f"(d[1]), "+f"(d[2]), "+f"(d[3]), "+f"(d[4]), "+f"(d[5]), "+f"(d[6]), "+f"(d[7]),
      "+f"(d[8]), "+f"(d[9]), "+f"(d[10]), "+f"(d[11]), "+f"(d[12]), "+f"(d[13]), "+f"(d[14]), "+f"(d[15]),
      "+f"(d[16]), "+f"(d[17]), "+f"(d[18]), "+f"(d[19]), "+f"(d[20]), "+f"(d[21]), "+f"(d[22]), "+f"(d[23]),
      "+f"(d[24]), "+f"(d[25]), "+f"(d[26]), "+f"(d[27]), "+f"(d[28]), "+f"(d[29]), "+f"(d[30]), "+f"(d[31]),
      "+f"(d[32]), "+f"(d[33]), "+f"(d[34]), "+f"(d[35]), "+f"(d[36]), "+f"(d[37]), "+f"(d[38]), "+f"(d[39]),
      "+f"(d[40]), "+f"(d[41]), "+f"(d[42]), "+f"(d[43]), "+f"(d[44]), "+f"(d[45]), "+f"(d[46]), "+f"(d[47]),
      "+f"(d[48]), "+f"(d[49]), "+f"(d[50]), "+f"(d[51]), "+f"(d[52]), "+f"(d[53]), "+f"(d[54]), "+f"(d[55]),
      "+f"(d[56]), "+f"(d[57]), "+f"(d[58]), "+f"(d[59]), "+f"(d[60]), "+f"(d[61]), "+f"(d[62]), "+f"(d[63])
    : "l"(descA), "l"(descB), "r"(scaleD));
}

__device__ __forceinline__ void wgmma_n128_kn(float (&d)[64], uint64_t descA, uint64_t descB, int scaleD) {
  asm volatile(
    "{\n.reg .pred p;\nsetp.ne.b32 p, %66, 0;\n"
    "wgmma.mma_async.sync.aligned.m64n128k16.f32.bf16.bf16 "
    "{%0, %1, %2, %3, %4, %5, %6, %7, %8, %9, %10, %11, %12, %13, %14, %15, "
    "%16, %17, %18, %19, %20, %21, %22, %23, %24, %25, %26, %27, %28, %29, %30, %31, "
    "%32, %33, %34, %35, %36, %37, %38, %39, %40, %41, %42, %43, %44, %45, %46, %47, "
    "%48, %49, %50, %51, %52, %53, %54, %55, %56, %57, %58, %59, %60, %61, %62, %63}, "
    "%64, %65, p, 1, 1, 0, 1;\n}\n"
    : "+f"(d[0]), "+f"(d[1]), "+f"(d[2]), "+f"(d[3]), "+f"(d[4]), "+f"(d[5]), "+f"(d[6]), "+f"(d[7]),
      "+f"(d[8]), "+f"(d[9]), "+f"(d[10]), "+f"(d[11]), "+f"(d[12]), "+f"(d[13]), "+f"(d[14]), "+f"(d[15]),
      "+f"(d[16]), "+f"(d[17]), "+f"(d[18]), "+f"(d[19]), "+f"(d[20]), "+f"(d[21]), "+f"(d[22]), "+f"(d[23]),
      "+f"(d[24]), "+f"(d[25]), "+f"(d[26]), "+f"(d[27]), "+f"(d[28]), "+f"(d[29]), "+f"(d[30]), "+f"(d[31]),
      "+f"(d[32]), "+f"(d[33]), "+f"(d[34]), "+f"(d[35]), "+f"(d[36]), "+f"(d[37]), "+f"(d[38]), "+f"(d[39]),
      "+f"(d[40]), "+f"(d[41]), "+f"(d[42]), "+f"(d[43]), "+f"(d[44]), "+f"(d[45]), "+f"(d[46]), "+f"(d[47]),
      "+f"(d[48]), "+f"(d[49]), "+f"(d[50]), "+f"(d[51]), "+f"(d[52]), "+f"(d[53]), "+f"(d[54]), "+f"(d[55]),
      "+f"(d[56]), "+f"(d[57]), "+f"(d[58]), "+f"(d[59]), "+f"(d[60]), "+f"(d[61]), "+f"(d[62]), "+f"(d[63])
    : "l"(descA), "l"(descB), "r"(scaleD));
}

__device__ __forceinline__ void wgmma_n128_mk(float (&d)[64], uint64_t descA, uint64_t descB, int scaleD) {
  asm volatile(
    "{\n.reg .pred p;\nsetp.ne.b32 p, %66, 0;\n"
    "wgmma.mma_async.sync.aligned.m64n128k16.f32.bf16.bf16 "
    "{%0, %1, %2, %3, %4, %5, %6, %7, %8, %9, %10, %11, %12, %13, %14, %15, "
    "%16, %17, %18, %19, %20, %21, %22, %23, %24, %25, %26, %27, %28, %29, %30, %31, "
    "%32, %33, %34, %35, %36, %37, %38, %39, %40, %41, %42, %43, %44, %45, %46, %47, "
    "%48, %49, %50, %51, %52, %53, %54, %55, %56, %57, %58, %59, %60, %61, %62, %63}, "
    "%64, %65, p, 1, 1, 1, 0;\n}\n"
    : "+f"(d[0]), "+f"(d[1]), "+f"(d[2]), "+f"(d[3]), "+f"(d[4]), "+f"(d[5]), "+f"(d[6]), "+f"(d[7]),
      "+f"(d[8]), "+f"(d[9]), "+f"(d[10]), "+f"(d[11]), "+f"(d[12]), "+f"(d[13]), "+f"(d[14]), "+f"(d[15]),
      "+f"(d[16]), "+f"(d[17]), "+f"(d[18]), "+f"(d[19]), "+f"(d[20]), "+f"(d[21]), "+f"(d[22]), "+f"(d[23]),
      "+f"(d[24]), "+f"(d[25]), "+f"(d[26]), "+f"(d[27]), "+f"(d[28]), "+f"(d[29]), "+f"(d[30]), "+f"(d[31]),
      "+f"(d[32]), "+f"(d[33]), "+f"(d[34]), "+f"(d[35]), "+f"(d[36]), "+f"(d[37]), "+f"(d[38]), "+f"(d[39]),
      "+f"(d[40]), "+f"(d[41]), "+f"(d[42]), "+f"(d[43]), "+f"(d[44]), "+f"(d[45]), "+f"(d[46]), "+f"(d[47]),
      "+f"(d[48]), "+f"(d[49]), "+f"(d[50]), "+f"(d[51]), "+f"(d[52]), "+f"(d[53]), "+f"(d[54]), "+f"(d[55]),
      "+f"(d[56]), "+f"(d[57]), "+f"(d[58]), "+f"(d[59]), "+f"(d[60]), "+f"(d[61]), "+f"(d[62]), "+f"(d[63])
    : "l"(descA), "l"(descB), "r"(scaleD));
}

__device__ __forceinline__ void wgmma_n32_mn(float (&d)[16], uint64_t descA, uint64_t descB, int scaleD) {
  asm volatile(
    "{\n.reg .pred p;\nsetp.ne.b32 p, %18, 0;\n"
    "wgmma.mma_async.sync.aligned.m64n32k16.f32.bf16.bf16 "
    "{%0, %1, %2, %3, %4, %5, %6, %7, %8, %9, %10, %11, %12, %13, %14, %15}, "
    "%16, %17, p, 1, 1, 1, 1;\n}\n"
    : "+f"(d[0]), "+f"(d[1]), "+f"(d[2]), "+f"(d[3]), "+f"(d[4]), "+f"(d[5]), "+f"(d[6]), "+f"(d[7]),
      "+f"(d[8]), "+f"(d[9]), "+f"(d[10]), "+f"(d[11]), "+f"(d[12]), "+f"(d[13]), "+f"(d[14]), "+f"(d[15])
    : "l"(descA), "l"(descB), "r"(scaleD));
}

__device__ __forceinline__ void wgmma_n8_mk(float (&d)[4], uint64_t descA, uint64_t descB, int scaleD) {
  asm volatile(
    "{\n.reg .pred p;\nsetp.ne.b32 p, %6, 0;\n"
    "wgmma.mma_async.sync.aligned.m64n8k16.f32.bf16.bf16 "
    "{%0, %1, %2, %3}, "
    "%4, %5, p, 1, 1, 1, 0;\n}\n"
    : "+f"(d[0]), "+f"(d[1]), "+f"(d[2]), "+f"(d[3])
    : "l"(descA), "l"(descB), "r"(scaleD));
}

__device__ __forceinline__ void wgmma_n40_rs(float (&d)[20], uint32_t a0, uint32_t a1, uint32_t a2, uint32_t a3, uint64_t descB, int scaleD) {
  asm volatile(
    "{\n.reg .pred p;\nsetp.ne.b32 p, %25, 0;\n"
    "wgmma.mma_async.sync.aligned.m64n40k16.f32.bf16.bf16 "
    "{%0, %1, %2, %3, %4, %5, %6, %7, %8, %9, %10, %11, %12, %13, %14, %15, "
    "%16, %17, %18, %19}, "
    "{%20, %21, %22, %23}, %24, p, 1, 1, 0;\n}\n"
    : "+f"(d[0]), "+f"(d[1]), "+f"(d[2]), "+f"(d[3]), "+f"(d[4]), "+f"(d[5]), "+f"(d[6]), "+f"(d[7]),
      "+f"(d[8]), "+f"(d[9]), "+f"(d[10]), "+f"(d[11]), "+f"(d[12]), "+f"(d[13]), "+f"(d[14]), "+f"(d[15]),
      "+f"(d[16]), "+f"(d[17]), "+f"(d[18]), "+f"(d[19])
    : "r"(a0), "r"(a1), "r"(a2), "r"(a3), "l"(descB), "r"(scaleD));
}

constexpr uint64_t DESC_K = desc_base(16, 1024, 1);
constexpr uint64_t DESC_MN = desc_base(8192, 1024, 1);
constexpr uint64_t DESC_ONES = desc_base(128, 256, 0);

enum : int { BAR_FULL = 0, BAR_EMPTY = 3, BAR_STG_FULL = 6, BAR_STG_EMPTY = 7, BAR_O = 8, BAR_X = 12, NBAR = 13 };

struct Pipe { int stage; uint32_t phase; };
__device__ __forceinline__ void pipe_next(Pipe& p) { if (++p.stage == STAGES) { p.stage = 0; p.phase ^= 1; } }

template <int VAR>
__device__ __forceinline__ void mma_tile(float (&acc)[128], int nkb, Pipe& p, uint32_t sb, int wg, bool leader) {
  const uint32_t bars = sb + SM_BAR;
  float (&lo)[64] = *reinterpret_cast<float (*)[64]>(&acc[0]);
  float (&hi)[64] = *reinterpret_cast<float (*)[64]>(&acc[64]);
  int prev = 0;
  for (int kb = 0; kb < nkb; kb++) {
    mbar_wait(bars + (BAR_FULL + p.stage) * 8, p.phase);
    uint32_t sa = sb + p.stage * STAGE_BYTES + wg * 8192;
    const uint32_t sbb = sb + p.stage * STAGE_BYTES + 16384;
    if (VAR == 3 && kb < 4) {
      mbar_wait(bars + (BAR_O + kb) * 8, 0);
      sa = sb + SM_STG + kb * 16384 + wg * 8192;
    }
    wgmma_fence();
#pragma unroll
    for (int k = 0; k < 4; k++) {
      const int sc = (kb | k) != 0;
      if (VAR == 0) {
        wgmma_n128_kk(lo, make_desc(sa + k * 32, DESC_K), make_desc(sbb + k * 32, DESC_K), sc);
        wgmma_n128_kk(hi, make_desc(sa + k * 32, DESC_K), make_desc(sbb + 16384 + k * 32, DESC_K), sc);
      } else if (VAR == 2) {
        wgmma_n128_mk(lo, make_desc(sa + k * 2048, DESC_MN), make_desc(sbb + k * 32, DESC_K), sc);
        wgmma_n128_mk(hi, make_desc(sa + k * 2048, DESC_MN), make_desc(sbb + 16384 + k * 32, DESC_K), sc);
      } else {
        wgmma_n128_kn(lo, make_desc(sa + k * 32, DESC_K), make_desc(sbb + k * 2048, DESC_MN), sc);
        wgmma_n128_kn(hi, make_desc(sa + k * 32, DESC_K), make_desc(sbb + 16384 + k * 2048, DESC_MN), sc);
      }
    }
    wgmma_commit();
    if (kb > 0) {
      wgmma_wait<1>();
      if (leader) mbar_arrive(bars + (BAR_EMPTY + prev) * 8);
    }
    prev = p.stage;
    pipe_next(p);
  }
  wgmma_wait<0>();
  if (leader) mbar_arrive(bars + (BAR_EMPTY + prev) * 8);
  fence_regs(acc);
}

__device__ __forceinline__ void dump_tile(const float (&acc)[128], uint32_t sb, int wg, int w, int lane) {
  const int mat = lane >> 3, r8 = lane & 7;
  const uint32_t rowaddr = sb + SM_STG + (wg * 64 + w * 16 + (mat & 1) * 8 + r8) * 128;
#pragma unroll
  for (int j = 0; j < 32; j += 2) {
    const int jj = j + (mat >> 1);
    const uint32_t addr = rowaddr + (j >> 3) * 16384 + (((jj & 7) ^ r8) << 4);
    stsm4(addr, pack_bf16(acc[4 * j], acc[4 * j + 1]), pack_bf16(acc[4 * j + 2], acc[4 * j + 3]),
          pack_bf16(acc[4 * j + 4], acc[4 * j + 5]), pack_bf16(acc[4 * j + 6], acc[4 * j + 7]));
  }
}

template <bool WITH_X>
__device__ __forceinline__ void final_store(float (&acc)[128], const Params& P, uint32_t sb, int wg, int w, int lane, int row0, int col0,
                                            int dcol0) {
  const int g = lane >> 2, q = lane & 3;
  const uint32_t st = sb + wg * 65536;
  const int r = w * 16 + g;
#pragma unroll
  for (int b = 0; b < 8; b++) {
#pragma unroll
    for (int j = 0; j < 4; j++) {
      const int jb = b * 4 + j;
      float v0 = acc[4 * jb], v1 = acc[4 * jb + 1], v2 = acc[4 * jb + 2], v3 = acc[4 * jb + 3];
      if (WITH_X) {
        const uint32_t xa = sb + SM_STG + (jb >> 3) * 16384 + (wg * 64 + r) * 128 + (((jb & 7) ^ (r & 7)) << 4) + q * 4;
        const uint32_t x0 = lds32(xa), x1 = lds32(xa + 1024);
        const uint32_t dd = *reinterpret_cast<const uint32_t*>(P.dskip + dcol0 + jb * 8 + q * 2);
        const float d0 = bf_lo(dd), d1 = bf_hi(dd);
        const uint32_t p0 = pack_bf16(bf_lo(x0) * d0, bf_hi(x0) * d1), p1 = pack_bf16(bf_lo(x1) * d0, bf_hi(x1) * d1);
        v0 += bf_lo(p0); v1 += bf_hi(p0); v2 += bf_lo(p1); v3 += bf_hi(p1);
      }
      const uint32_t a = st + b * 8192 + r * 128 + (((j * 2 + (q >> 1)) ^ (r & 7)) << 4) + (q & 1) * 8;
      sts64f(a, v0, v1);
      sts64f(a + 1024, v2, v3);
    }
    fence_async_smem();
    bar_sync(3 + wg, 128);
    if (w == 0 && lane == 0) { tma_store(&P.mOut, st + b * 8192, col0 + b * 32, row0 + wg * 64); bulk_commit(); }
  }
  if (w == 0 && lane == 0) bulk_wait_all();
}

__device__ __forceinline__ void epi_setup(const Params& P, int b, int ew, int lane, uint32_t sb) {
  const int hs = b >> 1, h = hs & 31, col0 = (hs >> 5) * 1024 + h * 32;
  const int g = lane >> 2, q = lane & 3;
  uint32_t bf[2][4][2];
  const unsigned short* wp = reinterpret_cast<const unsigned short*>(P.wphi) + h * 1024;
#pragma unroll
  for (int ks = 0; ks < 2; ks++)
#pragma unroll
    for (int j = 0; j < 4; j++)
#pragma unroll
      for (int e = 0; e < 2; e++) {
        const int k = ks * 16 + e * 8 + 2 * q, n = j * 8 + g;
        bf[ks][j][e] = (uint32_t)wp[k * 32 + n] | ((uint32_t)wp[(k + 1) * 32 + n] << 16);
      }
#pragma unroll
  for (int i = 0; i < 4; i++) {
    const int row = (b & 1) * 512 + ew * 64 + i * 16 + g;
    const uint32_t* src = reinterpret_cast<const uint32_t*>(P.wqkv + (size_t)row * 3072 + col0) + q;
    uint32_t a[2][4];
#pragma unroll
    for (int ks = 0; ks < 2; ks++) {
      a[ks][0] = __ldg(src + ks * 8);
      a[ks][1] = __ldg(src + 8 * 1536 + ks * 8);
      a[ks][2] = __ldg(src + ks * 8 + 4);
      a[ks][3] = __ldg(src + 8 * 1536 + ks * 8 + 4);
    }
    uint32_t* dst = reinterpret_cast<uint32_t*>(g_Wf + (size_t)row * 2048 + col0) + q;
#pragma unroll
    for (int j = 0; j < 4; j++) {
      float c[4] = {0.f, 0.f, 0.f, 0.f};
      mma16816(c, a[0][0], a[0][1], a[0][2], a[0][3], bf[0][j][0], bf[0][j][1]);
      mma16816(c, a[1][0], a[1][1], a[1][2], a[1][3], bf[1][j][0], bf[1][j][1]);
      dst[j * 4] = pack_bf16(c[0], c[1]);
      dst[8 * 1024 + j * 4] = pack_bf16(c[2], c[3]);
    }
  }
  const int et = ew * 32 + lane;
  if (et < 128) reinterpret_cast<float4*>(g_kv)[b * 128 + et] = make_float4(0.f, 0.f, 0.f, 0.f);
  else if (et < 132) reinterpret_cast<float4*>(g_z)[b * 4 + et - 128] = make_float4(0.f, 0.f, 0.f, 0.f);
  if (et < 64) asm volatile("st.shared.u32 [%0], %1;" :: "r"(sb + SM_ONES + et * 4), "r"(0x3F803F80u) : "memory");
  __threadfence();
  fence_async_all();
  bar_sync(2, 256);
  if (et == 0) red_release_add(&g_cnt_setup, 1);
}

__device__ __forceinline__ void cmul(float& ar, float& ai, float br, float bi) {
  const float r = ar * br - ai * bi, i = ar * bi + ai * br;
  ar = r; ai = i;
}

__device__ __forceinline__ void epi_scan(const Params& P, int b, int ew, int lane, uint32_t sb, uint32_t ep) {
  const int cb = b & 15, tb = b >> 4;
  const int seg = ew >> 1, c = (ew & 1) * 32 + lane, ch = cb * 64 + c;
  const float Lre = __bfloat162float(P.lam_re[ch]), Lim = __bfloat162float(P.lam_im[ch]);
  const float dt = __bfloat162float(__float2bfloat16(expf(__bfloat162float(P.log_dt[ch]))));
  float sn, cs;
  sincosf(dt * Lim, &sn, &cs);
  const float mag = expf(dt * Lre);
  const float lr = mag * cs, li = mag * sn;
  const float inv = 1.0f / (Lre * Lre + Lim * Lim);
  const float cr = 2.0f * ((lr - 1.0f) * Lre + li * Lim) * inv, ci = 2.0f * (li * Lre - (lr - 1.0f) * Lim) * inv;
  float l64r = lr, l64i = li;
#pragma unroll
  for (int i = 0; i < 6; i++) cmul(l64r, l64i, l64r, l64i);
  float l256r = l64r, l256i = l64i;
  cmul(l256r, l256i, l256r, l256i);
  cmul(l256r, l256i, l256r, l256i);

  const uint32_t bars = sb + SM_BAR;
  mbar_wait(bars + BAR_STG_FULL * 8, 0);
  const uint32_t rre = sb + SM_STG + seg * 16384 + c * 128, rim = rre + 64 * 128;
  const int sw = c & 7;
  float sr = 0.f, si = 0.f;
#pragma unroll 2
  for (int j = 0; j < 8; j++) {
    const uint4 vr = lds128(rre + ((j ^ sw) << 4)), vi = lds128(rim + ((j ^ sw) << 4));
    const uint32_t wr[4] = {vr.x, vr.y, vr.z, vr.w}, wi[4] = {vi.x, vi.y, vi.z, vi.w};
#pragma unroll
    for (int e = 0; e < 8; e++) {
      const float ur = (e & 1) ? bf_hi(wr[e >> 1]) : bf_lo(wr[e >> 1]);
      const float ui = (e & 1) ? bf_hi(wi[e >> 1]) : bf_lo(wi[e >> 1]);
      const float nr = fmaf(lr, sr, fmaf(-li, si, ur));
      const float ni = fmaf(lr, si, fmaf(li, sr, ui));
      sr = nr; si = ni;
    }
  }
  const uint32_t sagg = sb + SM_P;
  sts64f(sagg + (seg * 64 + c) * 8, sr, si);
  bar_sync(2, 256);
  float pr = 0.f, pi = 0.f;
  for (int s = 0; s < seg; s++) {
    const float2 a = lds64f(sagg + (s * 64 + c) * 8);
    cmul(pr, pi, l64r, l64i);
    pr += a.x; pi += a.y;
  }
  const unsigned long long tag = (unsigned long long)(ep + 1) << 32;
  if (seg == 3 && tb < 7) {
    float tr = pr, ti = pi;
    cmul(tr, ti, l64r, l64i);
    tr += sr; ti += si;
    const unsigned long long w0 = tag | __float_as_uint(tr), w1 = tag | __float_as_uint(ti);
    asm volatile("st.relaxed.gpu.global.v2.u64 [%0], {%1, %2};" :: "l"(&g_agg[(cb * 8 + tb) * 64 + c]), "l"(w0), "l"(w1) : "memory");
  }
  float hr = 0.f, hi = 0.f;
  for (int j = 0; j < tb; j++) {
    unsigned long long w0, w1;
    uint32_t n = 0;
    const ulonglong2* src = &g_agg[(cb * 8 + j) * 64 + c];
    while (true) {
      asm volatile("ld.relaxed.gpu.global.v2.u64 {%0, %1}, [%2];" : "=l"(w0), "=l"(w1) : "l"(src) : "memory");
      if ((w0 >> 32) == (ep + 1) && (w1 >> 32) == (ep + 1)) break;
      if (++n > SPIN_LIMIT) __trap();
    }
    cmul(hr, hi, l256r, l256i);
    hr += __uint_as_float((uint32_t)w0); hi += __uint_as_float((uint32_t)w1);
  }
  for (int s = 0; s < seg; s++) cmul(hr, hi, l64r, l64i);
  float gr = hr + pr, gi = hi + pi;
#pragma unroll 2
  for (int j = 0; j < 8; j++) {
    const uint32_t ar = rre + ((j ^ sw) << 4), ai = rim + ((j ^ sw) << 4);
    const uint4 vr = lds128(ar), vi = lds128(ai);
    const uint32_t wr[4] = {vr.x, vr.y, vr.z, vr.w}, wi[4] = {vi.x, vi.y, vi.z, vi.w};
    uint32_t orr[4], oi[4];
#pragma unroll
    for (int e2 = 0; e2 < 4; e2++) {
      float h_r[2], h_i[2];
#pragma unroll
      for (int e = 0; e < 2; e++) {
        const float ur = e ? bf_hi(wr[e2]) : bf_lo(wr[e2]);
        const float ui = e ? bf_hi(wi[e2]) : bf_lo(wi[e2]);
        const float nr = fmaf(lr, gr, fmaf(-li, gi, ur));
        const float ni = fmaf(lr, gi, fmaf(li, gr, ui));
        gr = nr; gi = ni;
        h_r[e] = fmaf(cr, gr, -ci * gi);
        h_i[e] = -fmaf(cr, gi, ci * gr);
      }
      orr[e2] = pack_bf16(h_r[0], h_r[1]);
      oi[e2] = pack_bf16(h_i[0], h_i[1]);
    }
    sts128(ar, make_uint4(orr[0], orr[1], orr[2], orr[3]));
    sts128(ai, make_uint4(oi[0], oi[1], oi[2], oi[3]));
  }
  fence_async_smem();
  bar_sync(2, 256);
  if (ew == 0 && lane == 0) {
#pragma unroll
    for (int s = 0; s < 4; s++) {
      tma_store(&P.mHT, sb + SM_STG + s * 16384, tb * 256 + s * 64, cb * 128);
      tma_store(&P.mHT, sb + SM_STG + s * 16384 + 8192, tb * 256 + s * 64, cb * 128 + 64);
    }
    bulk_commit();
    bulk_wait_all();
    fence_async_all();
    __threadfence();
    red_release_add(&g_cnt_h[tb], 1);
    mbar_arrive(bars + BAR_STG_EMPTY * 8);
  }
}

__device__ __forceinline__ void quad_minmax(const uint32_t (&x)[8], uint32_t& mx, uint32_t& mn) {
  const uint32_t a = hmax2(hmax2(x[0], x[2]), hmax2(x[4], x[6])), bq = hmax2(hmax2(x[1], x[3]), hmax2(x[5], x[7]));
  const uint32_t c = hmin2(hmin2(x[0], x[2]), hmin2(x[4], x[6])), d = hmin2(hmin2(x[1], x[3]), hmin2(x[5], x[7]));
  mx = hmax2(__byte_perm(a, bq, 0x5410), __byte_perm(a, bq, 0x7632));
  mn = hmin2(__byte_perm(c, d, 0x5410), __byte_perm(c, d, 0x7632));
  mx = hmax2(mx, __shfl_xor_sync(0xffffffffu, mx, 1));
  mn = hmin2(mn, __shfl_xor_sync(0xffffffffu, mn, 1));
  mx = hmax2(mx, __shfl_xor_sync(0xffffffffu, mx, 2));
  mn = hmin2(mn, __shfl_xor_sync(0xffffffffu, mn, 2));
}

__device__ __forceinline__ float quad_sum(float v) {
  v += __shfl_xor_sync(0xffffffffu, v, 1);
  v += __shfl_xor_sync(0xffffffffu, v, 2);
  return v;
}

__device__ __forceinline__ void epi_kv(int b, int ew, int lane, uint32_t sb) {
  const int hq = b >> 4;
  const int e = ew >> 2, w = ew & 3;
  const uint32_t bars = sb + SM_BAR;
  const int mat = lane >> 3, r8 = lane & 7;
  const uint32_t rowoff = (e * 64 + w * 16 + (mat & 1) * 8 + r8) * 128;
  const int cadd = mat >> 1;
  mbar_wait(bars + BAR_STG_FULL * 8, 1);
#pragma unroll 1
  for (int hh = 0; hh < 4; hh++) {
    const uint32_t src = sb + SM_STG + (hh >> 1) * 16384 + rowoff;
    uint32_t x[8];
    ldsm4(src + ((((hh & 1) * 4 + cadd) ^ r8) << 4), x[0], x[1], x[2], x[3]);
    ldsm4(src + ((((hh & 1) * 4 + 2 + cadd) ^ r8) << 4), x[4], x[5], x[6], x[7]);
    uint32_t mx, mn;
    quad_minmax(x, mx, mn);
    const uint32_t dstbuf = (hh & 1) ? (sb + SM_STG + (hh >> 1) * 16384) : (sb + SM_P);
    const uint32_t dst = dstbuf + rowoff;
#pragma unroll
    for (int sgn = 0; sgn < 2; sgn++) {
      const float sc = sgn ? -LOG2E : LOG2E;
      const uint32_t m = sgn ? mn : mx;
      const float o0 = -sc * bf_lo(m), o1 = -sc * bf_hi(m);
      float ev[16];
      float s0 = 0.f, s1 = 0.f;
#pragma unroll
      for (int i = 0; i < 8; i++) {
        const float o = (i & 1) ? o1 : o0;
        ev[2 * i] = ex2(fmaf(bf_lo(x[i]), sc, o));
        ev[2 * i + 1] = ex2(fmaf(bf_hi(x[i]), sc, o));
        if (i & 1) s1 += ev[2 * i] + ev[2 * i + 1]; else s0 += ev[2 * i] + ev[2 * i + 1];
      }
      const float i0 = rcp(quad_sum(s0)), i1 = rcp(quad_sum(s1));
      uint32_t pk[8];
#pragma unroll
      for (int i = 0; i < 8; i++) {
        const float s = (i & 1) ? i1 : i0;
        pk[i] = pack_bf16(ev[2 * i] * s, ev[2 * i + 1] * s);
      }
      stsm4(dst + (((sgn * 4 + cadd) ^ r8) << 4), pk[0], pk[1], pk[2], pk[3]);
      stsm4(dst + (((sgn * 4 + 2 + cadd) ^ r8) << 4), pk[4], pk[5], pk[6], pk[7]);
    }
    fence_async_smem();
    bar_sync(2, 256);
    if (e == (hh & 1)) {
      const uint32_t vb = sb + SM_STG + (2 + (hh >> 1)) * 16384 + (hh & 1) * 64;
      float D[16], Z[4];
      wgmma_fence();
#pragma unroll
      for (int ks = 0; ks < 8; ks++) {
        wgmma_n32_mn(D, make_desc(dstbuf + ks * 2048, DESC_MN), make_desc(vb + ks * 2048, DESC_MN), ks != 0);
        wgmma_n8_mk(Z, make_desc(dstbuf + ks * 2048, DESC_MN), make_desc(sb + SM_ONES, DESC_ONES), ks != 0);
      }
      wgmma_commit();
      wgmma_wait<0>();
      fence_regs(D); fence_regs(Z);
      const int h = hq * 4 + hh, g = lane >> 2, q = lane & 3;
      float* kp = g_kv + (h * 64 + w * 16 + g) * 32 + q * 2;
#pragma unroll
      for (int j = 0; j < 4; j++) { red_add_v2(kp + j * 8, D[4 * j], D[4 * j + 1]); red_add_v2(kp + 256 + j * 8, D[4 * j + 2], D[4 * j + 3]); }
      if (q == 0) { atomicAdd(g_z + h * 64 + w * 16 + g, Z[0]); atomicAdd(g_z + h * 64 + w * 16 + g + 8, Z[2]); }
    }
  }
  __threadfence();
  bar_sync(2, 256);
  if (ew == 0 && lane == 0) {
    red_release_add(&g_cnt_kv[hq], 1);
    mbar_arrive(bars + BAR_STG_EMPTY * 8);
  }
}

__device__ __forceinline__ void epi_q(const Params& P, int b, int ew, int lane, uint32_t sb, uint32_t ep) {
  const int rb = b & 15, oct = b >> 4;
  const int e = ew >> 2, w = ew & 3;
  const uint32_t bars = sb + SM_BAR;
  const int mat = lane >> 3, r8 = lane & 7, cadd = mat >> 1;
  const uint32_t bq = sb + SM_P + e * 5120;
  const int t = w * 32 + lane;
  if (t < 56) sts128(bq + 33 * 128 + t * 16, make_uint4(0u, 0u, 0u, 0u));
  if (lane == 0) { wait_counter(&g_cnt_kv[2 * oct], (ep + 1) * 16); wait_counter(&g_cnt_kv[2 * oct + 1], (ep + 1) * 16); }
  __syncwarp();
  mbar_wait(bars + BAR_STG_FULL * 8, 0);
#pragma unroll 1
  for (int kb = 0; kb < 4; kb++) {
    const int h = oct * 8 + kb * 2 + e;
    {
      const float* src = g_kv + h * 2048 + lane;
#pragma unroll
      for (int c2 = 0; c2 < 2; c2++) {
        const int fc = w * 2 + c2;
        float v[8];
#pragma unroll
        for (int i = 0; i < 8; i++) v[i] = __ldcg(src + (fc * 8 + i) * 32);
        sts128(bq + lane * 128 + ((fc ^ r8) << 4),
               make_uint4(pack_bf16(v[0], v[1]), pack_bf16(v[2], v[3]), pack_bf16(v[4], v[5]), pack_bf16(v[6], v[7])));
      }
      if (w == 0 && lane < 8) {
        const float4 z0 = __ldcg(reinterpret_cast<const float4*>(g_z + h * 64 + lane * 8)),
                     z1 = __ldcg(reinterpret_cast<const float4*>(g_z + h * 64 + lane * 8 + 4));
        sts128(bq + 32 * 128 + (lane << 4),
               make_uint4(pack_bf16(z0.x, z0.y), pack_bf16(z0.z, z0.w), pack_bf16(z1.x, z1.y), pack_bf16(z1.z, z1.w)));
      }
      fence_async_smem();
      bar_sync(5 + e, 128);
    }
#pragma unroll 1
    for (int mh = 0; mh < 2; mh++) {
      const uint32_t src = sb + SM_STG + kb * 16384 + (mh * 64 + w * 16 + (mat & 1) * 8 + r8) * 128;
      const uint32_t a0 = src + (((e * 4 + cadd) ^ r8) << 4), a1 = src + (((e * 4 + 2 + cadd) ^ r8) << 4);
      uint32_t x[8];
      ldsm4(a0, x[0], x[1], x[2], x[3]);
      ldsm4(a1, x[4], x[5], x[6], x[7]);
      uint32_t mx, mn;
      quad_minmax(x, mx, mn);
      uint32_t A[16];
#pragma unroll
      for (int sgn = 0; sgn < 2; sgn++) {
        const float sc = sgn ? -LOG2E : LOG2E;
        const uint32_t m = sgn ? mn : mx;
        const float o0 = -sc * bf_lo(m), o1 = -sc * bf_hi(m);
        float ev[16];
        float s0 = 0.f, s1 = 0.f;
#pragma unroll
        for (int i = 0; i < 8; i++) {
          const float o = (i & 1) ? o1 : o0;
          ev[2 * i] = ex2(fmaf(bf_lo(x[i]), sc, o));
          ev[2 * i + 1] = ex2(fmaf(bf_hi(x[i]), sc, o));
          if (i & 1) s1 += ev[2 * i] + ev[2 * i + 1]; else s0 += ev[2 * i] + ev[2 * i + 1];
        }
        const float i0 = rcp(quad_sum(s0)), i1 = rcp(quad_sum(s1));
#pragma unroll
        for (int i = 0; i < 8; i++) {
          const float s = (i & 1) ? i1 : i0;
          A[sgn * 8 + i] = pack_bf16(ev[2 * i] * s, ev[2 * i + 1] * s);
        }
      }
      float D[20];
      wgmma_fence();
#pragma unroll
      for (int ks = 0; ks < 4; ks++)
        wgmma_n40_rs(D, A[4 * ks], A[4 * ks + 1], A[4 * ks + 2], A[4 * ks + 3], make_desc(bq + ks * 32, DESC_K), ks != 0);
      wgmma_commit();
      wgmma_wait<0>();
      fence_regs(D);
      const float d0 = __frcp_rn(__shfl_sync(0xffffffffu, D[16], lane & ~3) + 1e-6f);
      const float d1 = __frcp_rn(__shfl_sync(0xffffffffu, D[18], lane & ~3) + 1e-6f);
      uint32_t o[8];
#pragma unroll
      for (int j = 0; j < 4; j++) {
        const int i = (j >> 1) * 4 + (j & 1) * 2;
        o[i] = pack_bf16(D[4 * j] * d0, D[4 * j + 1] * d0);
        o[i + 1] = pack_bf16(D[4 * j + 2] * d1, D[4 * j + 3] * d1);
      }
      stsm4(a0, o[0], o[1], o[2], o[3]);
      stsm4(a1, o[4], o[5], o[6], o[7]);
    }
    fence_async_smem();
    bar_sync(2, 256);
    if (ew == 0 && lane == 0) {
      mbar_arrive(bars + (BAR_O + kb) * 8);
      if (kb > 0) { bulk_wait_all(); fence_async_all(); __threadfence(); red_release_add(&g_cnt_o[rb * 4 + oct], 1); }
      tma_store(&P.mO, sb + SM_STG + kb * 16384, oct * 256 + kb * 64, rb * 128);
      bulk_commit();
    }
  }
  if (ew == 0 && lane == 0) { bulk_wait_all(); fence_async_all(); __threadfence(); red_release_add(&g_cnt_o[rb * 4 + oct], 1); }
}

__device__ __forceinline__ uint32_t prod_acquire(Pipe& p, uint32_t sb, uint32_t bytes) {
  const uint32_t bars = sb + SM_BAR;
  mbar_wait(bars + (BAR_EMPTY + p.stage) * 8, p.phase ^ 1);
  mbar_expect_tx(bars + (BAR_FULL + p.stage) * 8, bytes);
  return sb + p.stage * STAGE_BYTES;
}

__device__ __forceinline__ void producer(const Params& P, int b, uint32_t sb, uint32_t ep) {
  const uint32_t bars = sb + SM_BAR;
  Pipe p{0, 0};
  {
    const int cb = b & 15, tb = b >> 4;
    for (int kb = 0; kb < 16; kb++) {
      const uint32_t st = prod_acquire(p, sb, STAGE_BYTES), fb = bars + (BAR_FULL + p.stage) * 8;
      tma_load(st, &P.mBre, kb * 64, cb * 64, fb);
      tma_load(st + 8192, &P.mBim, kb * 64, cb * 64, fb);
      tma_load(st + 16384, &P.mBxB, kb * 64, tb * 256, fb);
      pipe_next(p);
    }
  }
  const int rb = b & 15, hi = b >> 4;
  wait_counter(&g_cnt_setup, (ep + 1) * NCTA);
  fence_async_all();
  for (int kb = 0; kb < 16; kb++) {
    const uint32_t st = prod_acquire(p, sb, STAGE_BYTES), fb = bars + (BAR_FULL + p.stage) * 8;
    tma_load(st, &P.mAx, kb * 64, rb * 128, fb);
    tma_load(st + 16384, &P.mWf, 1024 + hi * 128, kb * 64, fb);
    tma_load(st + 24576, &P.mWf, 1024 + hi * 128 + 64, kb * 64, fb);
    tma_load(st + 32768, &P.mWv, 2048 + hi * 128, kb * 64, fb);
    tma_load(st + 40960, &P.mWv, 2048 + hi * 128 + 64, kb * 64, fb);
    pipe_next(p);
  }
  if (b < 64) {
    const int oct = hi;
    for (int kb = 0; kb < 16; kb++) {
      const uint32_t st = prod_acquire(p, sb, STAGE_BYTES), fb = bars + (BAR_FULL + p.stage) * 8;
      tma_load(st, &P.mAx, kb * 64, rb * 128, fb);
#pragma unroll
      for (int j = 0; j < 4; j++) tma_load(st + 16384 + j * 8192, &P.mWf, oct * 256 + j * 64, kb * 64, fb);
      pipe_next(p);
    }
    for (int i = 0; i < 16; i++) {
      int koff;
      const bool own = i < 4;
      if (own) koff = oct * 256 + i * 64;
      else {
        const int r = i - 4, kb = r / 3, o2 = (oct + 1 + r % 3) & 3;
        koff = o2 * 256 + kb * 64;
        wait_counter(&g_cnt_o[rb * 4 + o2], ep * 4 + kb + 1);
        fence_async_all();
      }
      const uint32_t st = prod_acquire(p, sb, own ? 32768 : STAGE_BYTES), fb = bars + (BAR_FULL + p.stage) * 8;
      if (!own) tma_load(st, &P.mO, koff, rb * 128, fb);
#pragma unroll
      for (int j = 0; j < 4; j++) tma_load(st + 16384 + j * 8192, &P.mWo, oct * 256 + j * 64, koff, fb);
      pipe_next(p);
    }
  } else {
    const int db = hi - 4;
    wait_counter(&g_cnt_h[rb >> 1], (ep + 1) * 16);
    fence_async_all();
    for (int i = 0; i < 32; i++) {
      const uint32_t st = prod_acquire(p, sb, STAGE_BYTES), fb = bars + (BAR_FULL + p.stage) * 8;
      tma_load(st, &P.mHT, rb * 128, i * 64, fb);
      tma_load(st + 8192, &P.mHT, rb * 128 + 64, i * 64, fb);
      tma_load(st + 16384, (i & 1) ? &P.mCim : &P.mCre, (i >> 1) * 64, db * 256, fb);
      pipe_next(p);
      if (i == 8) {
        mbar_wait(bars + BAR_STG_EMPTY * 8, 1);
        mbar_expect_tx(bars + BAR_X * 8, 65536);
#pragma unroll
        for (int j = 0; j < 4; j++) tma_load(sb + SM_STG + j * 16384, &P.mBxT, db * 256 + j * 64, rb * 128, bars + BAR_X * 8);
      }
    }
  }
}

__global__ void __launch_bounds__(NTHREADS, 1) fused_kernel(const __grid_constant__ Params P) {
  extern __shared__ __align__(1024) uint8_t smem_raw[];
  const uint32_t sb = smem_u32(smem_raw);
  const int b = blockIdx.x, warp = threadIdx.x >> 5, lane = threadIdx.x & 31;
  const uint32_t bars = sb + SM_BAR;
  if (threadIdx.x == 512) {
    if (sb & 1023) __trap();
    for (int s = 0; s < STAGES; s++) { mbar_init(bars + (BAR_FULL + s) * 8, 1); mbar_init(bars + (BAR_EMPTY + s) * 8, 2); }
    mbar_init(bars + BAR_STG_FULL * 8, 8);
    mbar_init(bars + BAR_STG_EMPTY * 8, 1);
    for (int i = 0; i < 4; i++) mbar_init(bars + (BAR_O + i) * 8, 1);
    mbar_init(bars + BAR_X * 8, 1);
    asm volatile("fence.mbarrier_init.release.cluster;" ::: "memory");
    prefetch_map(&P.mBre); prefetch_map(&P.mBim); prefetch_map(&P.mBxB);
  }
  const uint32_t ep = *reinterpret_cast<volatile uint32_t*>(&g_epoch[b]);
  __syncthreads();

  if (warp < 8) {
    reg_alloc<REG_MMA>();
    const int wg = warp >> 2, w = warp & 3;
    const bool leader = (threadIdx.x & 127) == 0;
    float acc[128];
    Pipe p{0, 0};
    mma_tile<0>(acc, 16, p, sb, wg, leader);
    dump_tile(acc, sb, wg, w, lane);
    __syncwarp();
    if (lane == 0) mbar_arrive(bars + BAR_STG_FULL * 8);
    mma_tile<1>(acc, 16, p, sb, wg, leader);
    mbar_wait(bars + BAR_STG_EMPTY * 8, 0);
    dump_tile(acc, sb, wg, w, lane);
    fence_async_smem();
    __syncwarp();
    if (lane == 0) mbar_arrive(bars + BAR_STG_FULL * 8);
    const int rb = b & 15, hi = b >> 4;
    if (b < 64) {
      mma_tile<1>(acc, 16, p, sb, wg, leader);
      mbar_wait(bars + BAR_STG_EMPTY * 8, 1);
      dump_tile(acc, sb, wg, w, lane);
      __syncwarp();
      if (lane == 0) mbar_arrive(bars + BAR_STG_FULL * 8);
      mma_tile<3>(acc, 16, p, sb, wg, leader);
      bar_sync(1, 256);
      final_store<false>(acc, P, sb, wg, w, lane, rb * 128, hi * 256, 0);
    } else {
      mma_tile<2>(acc, 32, p, sb, wg, leader);
      mbar_wait(bars + BAR_X * 8, 0);
      bar_sync(1, 256);
      final_store<true>(acc, P, sb, wg, w, lane, rb * 128, 1024 + (hi - 4) * 256, (hi - 4) * 256);
    }
    if (threadIdx.x == 0) g_epoch[b] = ep + 1;
  } else if (warp < 16) {
    reg_dealloc<REG_EPI>();
    const int ew = warp - 8;
    epi_setup(P, b, ew, lane, sb);
    epi_scan(P, b, ew, lane, sb, ep);
    epi_kv(b, ew, lane, sb);
    if (b < 64) epi_q(P, b, ew, lane, sb, ep);
  } else {
    reg_dealloc<REG_PROD>();
    if (warp == 16 && lane == 0) producer(P, b, sb, ep);
  }
}

typedef CUresult (*EncodeTiledFn)(CUtensorMap*, CUtensorMapDataType, cuuint32_t, void*, const cuuint64_t*, const cuuint64_t*,
                                  const cuuint32_t*, const cuuint32_t*, CUtensorMapInterleave, CUtensorMapSwizzle,
                                  CUtensorMapL2promotion, CUtensorMapFloatOOBfill);

void make_map(EncodeTiledFn fn, CUtensorMap* m, const void* ptr, bool f32, uint64_t inner, uint64_t outer, uint32_t box_inner,
              uint32_t box_outer) {
  cuuint64_t dims[2] = {inner, outer};
  cuuint64_t strides[1] = {inner * (f32 ? 4 : 2)};
  cuuint32_t box[2] = {box_inner, box_outer};
  cuuint32_t es[2] = {1, 1};
  fn(m, f32 ? CU_TENSOR_MAP_DATA_TYPE_FLOAT32 : CU_TENSOR_MAP_DATA_TYPE_BFLOAT16, 2, const_cast<void*>(ptr), dims, strides, box, es,
     CU_TENSOR_MAP_INTERLEAVE_NONE, CU_TENSOR_MAP_SWIZZLE_128B, CU_TENSOR_MAP_L2_PROMOTION_L2_256B, CU_TENSOR_MAP_FLOAT_OOB_FILL_NONE);
}

}

extern "C" void kernel_launch(void* const* d_in, const int* in_sizes, int n_in, void* d_out, int out_size) {
  (void)in_sizes; (void)n_in; (void)out_size;
  static Params P;
  static void* cached[14];
  static bool ready = false;
  bool same = ready;
  for (int i = 0; i < 13 && same; i++) same = cached[i] == d_in[i];
  same = same && cached[13] == d_out;
  if (!same) {
    void* fnp = nullptr;
    cudaDriverEntryPointQueryResult st;
    cudaGetDriverEntryPoint("cuTensorMapEncodeTiled", &fnp, cudaEnableDefault, &st);
    EncodeTiledFn fn = (EncodeTiledFn)fnp;
    void *pWf, *pHT, *pO;
    cudaGetSymbolAddress(&pWf, g_Wf);
    cudaGetSymbolAddress(&pHT, g_hT);
    cudaGetSymbolAddress(&pO, g_o);
    make_map(fn, &P.mBre, d_in[7], false, 1024, 1024, 64, 64);
    make_map(fn, &P.mBim, d_in[8], false, 1024, 1024, 64, 64);
    make_map(fn, &P.mBxB, d_in[4], false, 1024, 2048, 64, 256);
    make_map(fn, &P.mAx, d_in[0], false, 1024, 2048, 64, 128);
    make_map(fn, &P.mWf, pWf, false, 2048, 1024, 64, 64);
    make_map(fn, &P.mWv, d_in[1], false, 3072, 1024, 64, 64);
    make_map(fn, &P.mHT, pHT, false, 2048, 2048, 64, 64);
    make_map(fn, &P.mCre, d_in[9], false, 1024, 1024, 64, 256);
    make_map(fn, &P.mCim, d_in[10], false, 1024, 1024, 64, 256);
    make_map(fn, &P.mO, pO, false, 1024, 2048, 64, 128);
    make_map(fn, &P.mWo, d_in[3], false, 1024, 1024, 64, 64);
    make_map(fn, &P.mOut, d_out, true, 2048, 2048, 32, 64);
    make_map(fn, &P.mBxT, d_in[4], false, 1024, 2048, 64, 128);
    P.wqkv = (const __nv_bfloat16*)d_in[1];
    P.wphi = (const __nv_bfloat16*)d_in[2];
    P.lam_re = (const __nv_bfloat16*)d_in[5];
    P.lam_im = (const __nv_bfloat16*)d_in[6];
    P.log_dt = (const __nv_bfloat16*)d_in[11];
    P.dskip = (const __nv_bfloat16*)d_in[12];
    P.ax = (const __nv_bfloat16*)d_in[0];
    P.cre = (const __nv_bfloat16*)d_in[9];
    P.cim = (const __nv_bfloat16*)d_in[10];
    P.wo = (const __nv_bfloat16*)d_in[3];
    cudaFuncSetAttribute(fused_kernel, cudaFuncAttributeMaxDynamicSharedMemorySize, SMEM_BYTES);
    for (int i = 0; i < 13; i++) cached[i] = d_in[i];
    cached[13] = d_out;
    ready = true;
  }
  fused_kernel<<<NCTA, NTHREADS, SMEM_BYTES>>>(P);
}
```

```cpp
#include <cuda_runtime.h>
#include <cuda_bf16.h>
#include <cuda.h>
#include <stdint.h>

namespace {

constexpr int NCTA = 128;
constexpr int NTHREADS = 384;
constexpr int REG_MMA = 216, REG_AUX = 72;
constexpr int STAGES = 4;
constexpr int STAGE_BYTES = 49152;
constexpr int SM_SCR = STAGES * STAGE_BYTES;
constexpr int SM_ZT = SM_SCR + 32768;
constexpr int SM_ONES = SM_ZT + 1024;
constexpr int SM_BAR = SM_ONES + 1024;
constexpr int SMEM_BYTES = SM_BAR + 320;
#define PF_DELAY 3000
#define START_PACE 200
constexpr float LOG2E = 1.4426950408889634f;
constexpr uint32_t SPIN_LIMIT = 1u << 21;

struct Params {
  CUtensorMap mBri, mBre, mBim, mBx, mAx, mWv, mHTs, mHT, mCre, mCim, mO, mWo, mOut, mBxT, mWphi4, mO64;
  const __nv_bfloat16 *lam_re, *lam_im, *log_dt, *dskip;
  int bmode;
};

__device__ __nv_bfloat16 g_hT[2048 * 2048];
__device__ __nv_bfloat16 g_o[2048 * 1024];
__device__ float g_kv[32 * 32 * 64];
__device__ float g_z[32 * 64];
__device__ uint4 g_kvb[32 * 320];
__device__ ulonglong2 g_agg[16 * 8 * 64];
__device__ uint32_t g_epoch[NCTA];
__device__ uint32_t g_cnt_zero;
__device__ uint32_t g_cnt_h[16];
__device__ uint32_t g_cnt_kv[8], g_kv_ready[8];
__device__ uint32_t g_cnt_o[64];

#define TK(i) do {} while (0)
#define TQ(i) do {} while (0)
#define TS(cond, i) do {} while (0)
#define TC(cond, i) do {} while (0)
__device__ __forceinline__ uint32_t smem_u32(const void* p) { return (uint32_t)__cvta_generic_to_shared(p); }
__device__ __forceinline__ void mbar_init(uint32_t bar, uint32_t count) {
  asm volatile("mbarrier.init.shared::cta.b64 [%0], %1;" :: "r"(bar), "r"(count) : "memory");
}
__device__ __forceinline__ void mbar_expect_tx(uint32_t bar, uint32_t bytes) {
  asm volatile("mbarrier.arrive.expect_tx.shared::cta.b64 _, [%0], %1;" :: "r"(bar), "r"(bytes) : "memory");
}
__device__ __forceinline__ void mbar_arrive(uint32_t bar) {
  asm volatile("mbarrier.arrive.shared::cta.b64 _, [%0];" :: "r"(bar) : "memory");
}
__device__ __forceinline__ bool mbar_try_wait(uint32_t bar, uint32_t parity) {
  uint32_t ok;
  asm volatile("{\n.reg .pred p;\nmbarrier.try_wait.parity.shared::cta.b64 p, [%1], %2;\nselp.u32 %0, 1, 0, p;\n}"
               : "=r"(ok) : "r"(bar), "r"(parity) : "memory");
  return ok;
}
__device__ __forceinline__ void mbar_wait(uint32_t bar, uint32_t parity) {
  uint32_t n = 0;
  while (!mbar_try_wait(bar, parity)) { if (++n > SPIN_LIMIT) __trap(); }
}
__device__ __forceinline__ void fence_async_smem() { asm volatile("fence.proxy.async.shared::cta;" ::: "memory"); }
__device__ __forceinline__ void fence_async_global() { asm volatile("fence.proxy.async.global;" ::: "memory"); }
__device__ __forceinline__ void bar_sync(int id, int n) { asm volatile("bar.sync %0, %1;" :: "r"(id), "r"(n) : "memory"); }

__device__ __forceinline__ void tma_load(uint32_t dst, const CUtensorMap* map, int c0, int c1, uint32_t bar) {
  asm volatile("cp.async.bulk.tensor.2d.shared::cluster.global.mbarrier::complete_tx::bytes [%0], [%1, {%3, %4}], [%2];"
               :: "r"(dst), "l"(map), "r"(bar), "r"(c0), "r"(c1) : "memory");
}
__device__ __forceinline__ void tma_load4(uint32_t dst, const CUtensorMap* map, int c0, int c1, int c2, int c3, uint32_t bar) {
  asm volatile("cp.async.bulk.tensor.4d.shared::cluster.global.mbarrier::complete_tx::bytes [%0], [%1, {%3, %4, %5, %6}], [%2];"
               :: "r"(dst), "l"(map), "r"(bar), "r"(c0), "r"(c1), "r"(c2), "r"(c3) : "memory");
}
__device__ __forceinline__ void tma_store3(const CUtensorMap* map, uint32_t src, int c0, int c1, int c2) {
  asm volatile("cp.async.bulk.tensor.3d.global.shared::cta.bulk_group [%0, {%2, %3, %4}], [%1];"
               :: "l"(map), "r"(src), "r"(c0), "r"(c1), "r"(c2) : "memory");
}
__device__ __forceinline__ void bulk_wait_read() { asm volatile("cp.async.bulk.wait_group.read 0;" ::: "memory"); }
__device__ __forceinline__ void tma_store(const CUtensorMap* map, uint32_t src, int c0, int c1) {
  asm volatile("cp.async.bulk.tensor.2d.global.shared::cta.bulk_group [%0, {%2, %3}], [%1];"
               :: "l"(map), "r"(src), "r"(c0), "r"(c1) : "memory");
}
__device__ __forceinline__ void bulk_commit() { asm volatile("cp.async.bulk.commit_group;" ::: "memory"); }
__device__ __forceinline__ void bulk_wait_all() { asm volatile("cp.async.bulk.wait_group 0;" ::: "memory"); }
__device__ __forceinline__ void prefetch_map(const CUtensorMap* map) {
  asm volatile("prefetch.tensormap [%0];" :: "l"(map) : "memory");
}
__device__ __forceinline__ void wgmma_fence() { asm volatile("wgmma.fence.sync.aligned;" ::: "memory"); }
__device__ __forceinline__ void wgmma_commit() { asm volatile("wgmma.commit_group.sync.aligned;" ::: "memory"); }
template <int N> __device__ __forceinline__ void wgmma_wait() { asm volatile("wgmma.wait_group.sync.aligned %0;" :: "n"(N) : "memory"); }
template <int R> __device__ __forceinline__ void fence_regs(float (&d)[R]) {
#pragma unroll
  for (int i = 0; i < R; i++) asm volatile("" : "+f"(d[i]) :: "memory");
}
__host__ __device__ constexpr uint64_t desc_base(uint32_t lbo, uint32_t sbo, uint32_t swz) {
  return ((uint64_t)((lbo & 0x3FFFF) >> 4) << 16) | ((uint64_t)((sbo & 0x3FFFF) >> 4) << 32) | ((uint64_t)swz << 62);
}
__device__ __forceinline__ uint64_t make_desc(uint32_t addr, uint64_t base) { return base | (uint64_t)((addr & 0x3FFFF) >> 4); }
template <int R> __device__ __forceinline__ void reg_alloc() { asm volatile("setmaxnreg.inc.sync.aligned.u32 %0;" :: "n"(R)); }
template <int R> __device__ __forceinline__ void reg_dealloc() { asm volatile("setmaxnreg.dec.sync.aligned.u32 %0;" :: "n"(R)); }

__device__ __forceinline__ void ldsm4(uint32_t addr, uint32_t& r0, uint32_t& r1, uint32_t& r2, uint32_t& r3) {
  asm volatile("ldmatrix.sync.aligned.m8n8.x4.shared.b16 {%0, %1, %2, %3}, [%4];"
               : "=r"(r0), "=r"(r1), "=r"(r2), "=r"(r3) : "r"(addr) : "memory");
}
__device__ __forceinline__ void stsm4(uint32_t addr, uint32_t r0, uint32_t r1, uint32_t r2, uint32_t r3) {
  asm volatile("stmatrix.sync.aligned.m8n8.x4.shared.b16 [%0], {%1, %2, %3, %4};"
               :: "r"(addr), "r"(r0), "r"(r1), "r"(r2), "r"(r3) : "memory");
}
__device__ __forceinline__ uint4 lds128(uint32_t addr) {
  uint4 v;
  asm volatile("ld.shared.v4.u32 {%0, %1, %2, %3}, [%4];" : "=r"(v.x), "=r"(v.y), "=r"(v.z), "=r"(v.w) : "r"(addr) : "memory");
  return v;
}
__device__ __forceinline__ void sts128(uint32_t addr, uint4 v) {
  asm volatile("st.shared.v4.u32 [%0], {%1, %2, %3, %4};" :: "r"(addr), "r"(v.x), "r"(v.y), "r"(v.z), "r"(v.w) : "memory");
}
__device__ __forceinline__ uint32_t lds32(uint32_t addr) {
  uint32_t v; asm volatile("ld.shared.u32 %0, [%1];" : "=r"(v) : "r"(addr) : "memory"); return v;
}
__device__ __forceinline__ void sts32f(uint32_t addr, float a) {
  asm volatile("st.shared.f32 [%0], %1;" :: "r"(addr), "f"(a) : "memory");
}
__device__ __forceinline__ void sts64f(uint32_t addr, float a, float b) {
  asm volatile("st.shared.v2.f32 [%0], {%1, %2};" :: "r"(addr), "f"(a), "f"(b) : "memory");
}
__device__ __forceinline__ uint32_t pack_bf16(float lo, float hi) {
  uint32_t r; asm("cvt.rn.bf16x2.f32 %0, %1, %2;" : "=r"(r) : "f"(hi), "f"(lo)); return r;
}
__device__ __forceinline__ float bf_lo(uint32_t v) { return __uint_as_float(v << 16); }
__device__ __forceinline__ float bf_hi(uint32_t v) { return __uint_as_float(v & 0xffff0000u); }
__device__ __forceinline__ float ex2(float x) { float y; asm("ex2.approx.ftz.f32 %0, %1;" : "=f"(y) : "f"(x)); return y; }
__device__ __forceinline__ float rcp(float x) { float y; asm("rcp.approx.ftz.f32 %0, %1;" : "=f"(y) : "f"(x)); return y; }
__device__ __forceinline__ uint32_t hmax2(uint32_t a, uint32_t b) { uint32_t r; asm("max.bf16x2 %0, %1, %2;" : "=r"(r) : "r"(a), "r"(b)); return r; }
__device__ __forceinline__ uint32_t hmin2(uint32_t a, uint32_t b) { uint32_t r; asm("min.bf16x2 %0, %1, %2;" : "=r"(r) : "r"(a), "r"(b)); return r; }
__device__ __forceinline__ uint32_t ld_acquire(const uint32_t* p) {
  uint32_t v; asm volatile("ld.acquire.gpu.global.u32 %0, [%1];" : "=r"(v) : "l"(p) : "memory"); return v;
}
__device__ __forceinline__ void red_release_add(uint32_t* p, uint32_t v) {
  asm volatile("red.release.gpu.global.add.u32 [%0], %1;" :: "l"(p), "r"(v) : "memory");
}
__device__ __forceinline__ uint32_t atom_add_acq_rel(uint32_t* p, uint32_t v) {
  uint32_t r; asm volatile("atom.acq_rel.gpu.global.add.u32 %0, [%1], %2;" : "=r"(r) : "l"(p), "r"(v) : "memory"); return r;
}
__device__ __forceinline__ void st_release(uint32_t* p, uint32_t v) {
  asm volatile("st.release.gpu.global.u32 [%0], %1;" :: "l"(p), "r"(v) : "memory");
}
__device__ __forceinline__ void bulk_load(uint32_t dst, const void* src, uint32_t bytes, uint32_t bar) {
  asm volatile("cp.async.bulk.shared::cluster.global.mbarrier::complete_tx::bytes [%0], [%1], %2, [%3];"
               :: "r"(dst), "l"(src), "r"(bytes), "r"(bar) : "memory");
}
__device__ __forceinline__ void wait_counter(const uint32_t* p, uint32_t target) {
  uint32_t n = 0;
  while ((int32_t)(ld_acquire(p) - target) < 0) { __nanosleep(32); if (++n > SPIN_LIMIT) __trap(); }
}

__device__ __forceinline__ void wgmma_n256_kk(float (&d)[128], uint64_t descA, uint64_t descB, int scaleD) {
  asm volatile(
    "{\n.reg .pred p;\nsetp.ne.b32 p, %130, 0;\n"
    "wgmma.mma_async.sync.aligned.m64n256k16.f32.bf16.bf16 "
    "{%0, %1, %2, %3, %4, %5, %6, %7, %8, %9, %10, %11, %12, %13, %14, %15, "
    "%16, %17, %18, %19, %20, %21, %22, %23, %24, %25, %26, %27, %28, %29, %30, %31, "
    "%32, %33, %34, %35, %36, %37, %38, %39, %40, %41, %42, %43, %44, %45, %46, %47, "
    "%48, %49, %50, %51, %52, %53, %54, %55, %56, %57, %58, %59, %60, %61, %62, %63, "
    "%64, %65, %66, %67, %68, %69, %70, %71, %72, %73, %74, %75, %76, %77, %78, %79, "
    "%80, %81, %82, %83, %84, %85, %86, %87, %88, %89, %90, %91, %92, %93, %94, %95, "
    "%96, %97, %98, %99, %100, %101, %102, %103, %104, %105, %106, %107, %108, %109, %110, %111, "
    "%112, %113, %114, %115, %116, %117, %118, %119, %120, %121, %122, %123, %124, %125, %126, %127}, "
    "%128, %129, p, 1, 1, 0, 0;\n}\n"
    : "+f"(d[0]), "+f"(d[1]), "+f"(d[2]), "+f"(d[3]), "+f"(d[4]), "+f"(d[5]), "+f"(d[6]), "+f"(d[7]),
      "+f"(d[8]), "+f"(d[9]), "+f"(d[10]), "+f"(d[11]), "+f"(d[12]), "+f"(d[13]), "+f"(d[14]), "+f"(d[15]),
      "+f"(d[16]), "+f"(d[17]), "+f"(d[18]), "+f"(d[19]), "+f"(d[20]), "+f"(d[21]), "+f"(d[22]), "+f"(d[23]),
      "+f"(d[24]), "+f"(d[25]), "+f"(d[26]), "+f"(d[27]), "+f"(d[28]), "+f"(d[29]), "+f"(d[30]), "+f"(d[31]),
      "+f"(d[32]), "+f"(d[33]), "+f"(d[34]), "+f"(d[35]), "+f"(d[36]), "+f"(d[37]), "+f"(d[38]), "+f"(d[39]),
      "+f"(d[40]), "+f"(d[41]), "+f"(d[42]), "+f"(d[43]), "+f"(d[44]), "+f"(d[45]), "+f"(d[46]), "+f"(d[47]),
      "+f"(d[48]), "+f"(d[49]), "+f"(d[50]), "+f"(d[51]), "+f"(d[52]), "+f"(d[53]), "+f"(d[54]), "+f"(d[55]),
      "+f"(d[56]), "+f"(d[57]), "+f"(d[58]), "+f"(d[59]), "+f"(d[60]), "+f"(d[61]), "+f"(d[62]), "+f"(d[63]),
      "+f"(d[64]), "+f"(d[65]), "+f"(d[66]), "+f"(d[67]), "+f"(d[68]), "+f"(d[69]), "+f"(d[70]), "+f"(d[71]),
      "+f"(d[72]), "+f"(d[73]), "+f"(d[74]), "+f"(d[75]), "+f"(d[76]), "+f"(d[77]), "+f"(d[78]), "+f"(d[79]),
      "+f"(d[80]), "+f"(d[81]), "+f"(d[82]), "+f"(d[83]), "+f"(d[84]), "+f"(d[85]), "+f"(d[86]), "+f"(d[87]),
      "+f"(d[88]), "+f"(d[89]), "+f"(d[90]), "+f"(d[91]), "+f"(d[92]), "+f"(d[93]), "+f"(d[94]), "+f"(d[95]),
      "+f"(d[96]), "+f"(d[97]), "+f"(d[98]), "+f"(d[99]), "+f"(d[100]), "+f"(d[101]), "+f"(d[102]), "+f"(d[103]),
      "+f"(d[104]), "+f"(d[105]), "+f"(d[106]), "+f"(d[107]), "+f"(d[108]), "+f"(d[109]), "+f"(d[110]), "+f"(d[111]),
      "+f"(d[112]), "+f"(d[113]), "+f"(d[114]), "+f"(d[115]), "+f"(d[116]), "+f"(d[117]), "+f"(d[118]), "+f"(d[119]),
      "+f"(d[120]), "+f"(d[121]), "+f"(d[122]), "+f"(d[123]), "+f"(d[124]), "+f"(d[125]), "+f"(d[126]), "+f"(d[127])
    : "l"(descA), "l"(descB), "r"(scaleD));
}

__device__ __forceinline__ void wgmma_n256_kn(float (&d)[128], uint64_t descA, uint64_t descB, int scaleD) {
  asm volatile(
    "{\n.reg .pred p;\nsetp.ne.b32 p, %130, 0;\n"
    "wgmma.mma_async.sync.aligned.m64n256k16.f32.bf16.bf16 "
    "{%0, %1, %2, %3, %4, %5, %6, %7, %8, %9, %10, %11, %12, %13, %14, %15, "
    "%16, %17, %18, %19, %20, %21, %22, %23, %24, %25, %26, %27, %28, %29, %30, %31, "
    "%32, %33, %34, %35, %36, %37, %38, %39, %40, %41, %42, %43, %44, %45, %46, %47, "
    "%48, %49, %50, %51, %52, %53, %54, %55, %56, %57, %58, %59, %60, %61, %62, %63, "
    "%64, %65, %66, %67, %68, %69, %70, %71, %72, %73, %74, %75, %76, %77, %78, %79, "
    "%80, %81, %82, %83, %84, %85, %86, %87, %88, %89, %90, %91, %92, %93, %94, %95, "
    "%96, %97, %98, %99, %100, %101, %102, %103, %104, %105, %106, %107, %108, %109, %110, %111, "
    "%112, %113, %114, %115, %116, %117, %118, %119, %120, %121, %122, %123, %124, %125, %126, %127}, "
    "%128, %129, p, 1, 1, 0, 1;\n}\n"
    : "+f"(d[0]), "+f"(d[1]), "+f"(d[2]), "+f"(d[3]), "+f"(d[4]), "+f"(d[5]), "+f"(d[6]), "+f"(d[7]),
      "+f"(d[8]), "+f"(d[9]), "+f"(d[10]), "+f"(d[11]), "+f"(d[12]), "+f"(d[13]), "+f"(d[14]), "+f"(d[15]),
      "+f"(d[16]), "+f"(d[17]), "+f"(d[18]), "+f"(d[19]), "+f"(d[20]), "+f"(d[21]), "+f"(d[22]), "+f"(d[23]),
      "+f"(d[24]), "+f"(d[25]), "+f"(d[26]), "+f"(d[27]), "+f"(d[28]), "+f"(d[29]), "+f"(d[30]), "+f"(d[31]),
      "+f"(d[32]), "+f"(d[33]), "+f"(d[34]), "+f"(d[35]), "+f"(d[36]), "+f"(d[37]), "+f"(d[38]), "+f"(d[39]),
      "+f"(d[40]), "+f"(d[41]), "+f"(d[42]), "+f"(d[43]), "+f"(d[44]), "+f"(d[45]), "+f"(d[46]), "+f"(d[47]),
      "+f"(d[48]), "+f"(d[49]), "+f"(d[50]), "+f"(d[51]), "+f"(d[52]), "+f"(d[53]), "+f"(d[54]), "+f"(d[55]),
      "+f"(d[56]), "+f"(d[57]), "+f"(d[58]), "+f"(d[59]), "+f"(d[60]), "+f"(d[61]), "+f"(d[62]), "+f"(d[63]),
      "+f"(d[64]), "+f"(d[65]), "+f"(d[66]), "+f"(d[67]), "+f"(d[68]), "+f"(d[69]), "+f"(d[70]), "+f"(d[71]),
      "+f"(d[72]), "+f"(d[73]), "+f"(d[74]), "+f"(d[75]), "+f"(d[76]), "+f"(d[77]), "+f"(d[78]), "+f"(d[79]),
      "+f"(d[80]), "+f"(d[81]), "+f"(d[82]), "+f"(d[83]), "+f"(d[84]), "+f"(d[85]), "+f"(d[86]), "+f"(d[87]),
      "+f"(d[88]), "+f"(d[89]), "+f"(d[90]), "+f"(d[91]), "+f"(d[92]), "+f"(d[93]), "+f"(d[94]), "+f"(d[95]),
      "+f"(d[96]), "+f"(d[97]), "+f"(d[98]), "+f"(d[99]), "+f"(d[100]), "+f"(d[101]), "+f"(d[102]), "+f"(d[103]),
      "+f"(d[104]), "+f"(d[105]), "+f"(d[106]), "+f"(d[107]), "+f"(d[108]), "+f"(d[109]), "+f"(d[110]), "+f"(d[111]),
      "+f"(d[112]), "+f"(d[113]), "+f"(d[114]), "+f"(d[115]), "+f"(d[116]), "+f"(d[117]), "+f"(d[118]), "+f"(d[119]),
      "+f"(d[120]), "+f"(d[121]), "+f"(d[122]), "+f"(d[123]), "+f"(d[124]), "+f"(d[125]), "+f"(d[126]), "+f"(d[127])
    : "l"(descA), "l"(descB), "r"(scaleD));
}

__device__ __forceinline__ void wgmma_n256_mk(float (&d)[128], uint64_t descA, uint64_t descB, int scaleD) {
  asm volatile(
    "{\n.reg .pred p;\nsetp.ne.b32 p, %130, 0;\n"
    "wgmma.mma_async.sync.aligned.m64n256k16.f32.bf16.bf16 "
    "{%0, %1, %2, %3, %4, %5, %6, %7, %8, %9, %10, %11, %12, %13, %14, %15, "
    "%16, %17, %18, %19, %20, %21, %22, %23, %24, %25, %26, %27, %28, %29, %30, %31, "
    "%32, %33, %34, %35, %36, %37, %38, %39, %40, %41, %42, %43, %44, %45, %46, %47, "
    "%48, %49, %50, %51, %52, %53, %54, %55, %56, %57, %58, %59, %60, %61, %62, %63, "
    "%64, %65, %66, %67, %68, %69, %70, %71, %72, %73, %74, %75, %76, %77, %78, %79, "
    "%80, %81, %82, %83, %84, %85, %86, %87, %88, %89, %90, %91, %92, %93, %94, %95, "
    "%96, %97, %98, %99, %100, %101, %102, %103, %104, %105, %106, %107, %108, %109, %110, %111, "
    "%112, %113, %114, %115, %116, %117, %118, %119, %120, %121, %122, %123, %124, %125, %126, %127}, "
    "%128, %129, p, 1, 1, 1, 0;\n}\n"
    : "+f"(d[0]), "+f"(d[1]), "+f"(d[2]), "+f"(d[3]), "+f"(d[4]), "+f"(d[5]), "+f"(d[6]), "+f"(d[7]),
      "+f"(d[8]), "+f"(d[9]), "+f"(d[10]), "+f"(d[11]), "+f"(d[12]), "+f"(d[13]), "+f"(d[14]), "+f"(d[15]),
      "+f"(d[16]), "+f"(d[17]), "+f"(d[18]), "+f"(d[19]), "+f"(d[20]), "+f"(d[21]), "+f"(d[22]), "+f"(d[23]),
      "+f"(d[24]), "+f"(d[25]), "+f"(d[26]), "+f"(d[27]), "+f"(d[28]), "+f"(d[29]), "+f"(d[30]), "+f"(d[31]),
      "+f"(d[32]), "+f"(d[33]), "+f"(d[34]), "+f"(d[35]), "+f"(d[36]), "+f"(d[37]), "+f"(d[38]), "+f"(d[39]),
      "+f"(d[40]), "+f"(d[41]), "+f"(d[42]), "+f"(d[43]), "+f"(d[44]), "+f"(d[45]), "+f"(d[46]), "+f"(d[47]),
      "+f"(d[48]), "+f"(d[49]), "+f"(d[50]), "+f"(d[51]), "+f"(d[52]), "+f"(d[53]), "+f"(d[54]), "+f"(d[55]),
      "+f"(d[56]), "+f"(d[57]), "+f"(d[58]), "+f"(d[59]), "+f"(d[60]), "+f"(d[61]), "+f"(d[62]), "+f"(d[63]),
      "+f"(d[64]), "+f"(d[65]), "+f"(d[66]), "+f"(d[67]), "+f"(d[68]), "+f"(d[69]), "+f"(d[70]), "+f"(d[71]),
      "+f"(d[72]), "+f"(d[73]), "+f"(d[74]), "+f"(d[75]), "+f"(d[76]), "+f"(d[77]), "+f"(d[78]), "+f"(d[79]),
      "+f"(d[80]), "+f"(d[81]), "+f"(d[82]), "+f"(d[83]), "+f"(d[84]), "+f"(d[85]), "+f"(d[86]), "+f"(d[87]),
      "+f"(d[88]), "+f"(d[89]), "+f"(d[90]), "+f"(d[91]), "+f"(d[92]), "+f"(d[93]), "+f"(d[94]), "+f"(d[95]),
      "+f"(d[96]), "+f"(d[97]), "+f"(d[98]), "+f"(d[99]), "+f"(d[100]), "+f"(d[101]), "+f"(d[102]), "+f"(d[103]),
      "+f"(d[104]), "+f"(d[105]), "+f"(d[106]), "+f"(d[107]), "+f"(d[108]), "+f"(d[109]), "+f"(d[110]), "+f"(d[111]),
      "+f"(d[112]), "+f"(d[113]), "+f"(d[114]), "+f"(d[115]), "+f"(d[116]), "+f"(d[117]), "+f"(d[118]), "+f"(d[119]),
      "+f"(d[120]), "+f"(d[121]), "+f"(d[122]), "+f"(d[123]), "+f"(d[124]), "+f"(d[125]), "+f"(d[126]), "+f"(d[127])
    : "l"(descA), "l"(descB), "r"(scaleD));
}

__device__ __forceinline__ void wgmma_n40_mn(float (&d)[20], uint64_t descA, uint64_t descB, int scaleD) {
  asm volatile(
    "{\n.reg .pred p;\nsetp.ne.b32 p, %22, 0;\n"
    "wgmma.mma_async.sync.aligned.m64n40k16.f32.bf16.bf16 "
    "{%0, %1, %2, %3, %4, %5, %6, %7, %8, %9, %10, %11, %12, %13, %14, %15, "
    "%16, %17, %18, %19}, "
    "%20, %21, p, 1, 1, 1, 1;\n}\n"
    : "+f"(d[0]), "+f"(d[1]), "+f"(d[2]), "+f"(d[3]), "+f"(d[4]), "+f"(d[5]), "+f"(d[6]), "+f"(d[7]),
      "+f"(d[8]), "+f"(d[9]), "+f"(d[10]), "+f"(d[11]), "+f"(d[12]), "+f"(d[13]), "+f"(d[14]), "+f"(d[15]),
      "+f"(d[16]), "+f"(d[17]), "+f"(d[18]), "+f"(d[19])
    : "l"(descA), "l"(descB), "r"(scaleD));
}

__device__ __forceinline__ void wgmma_n32_rs_n(float (&d)[16], uint32_t a0, uint32_t a1, uint32_t a2, uint32_t a3, uint64_t descB, int scaleD) {
  asm volatile(
    "{\n.reg .pred p;\nsetp.ne.b32 p, %21, 0;\n"
    "wgmma.mma_async.sync.aligned.m64n32k16.f32.bf16.bf16 "
    "{%0, %1, %2, %3, %4, %5, %6, %7, %8, %9, %10, %11, %12, %13, %14, %15}, "
    "{%16, %17, %18, %19}, %20, p, 1, 1, 1;\n}\n"
    : "+f"(d[0]), "+f"(d[1]), "+f"(d[2]), "+f"(d[3]), "+f"(d[4]), "+f"(d[5]), "+f"(d[6]), "+f"(d[7]),
      "+f"(d[8]), "+f"(d[9]), "+f"(d[10]), "+f"(d[11]), "+f"(d[12]), "+f"(d[13]), "+f"(d[14]), "+f"(d[15])
    : "r"(a0), "r"(a1), "r"(a2), "r"(a3), "l"(descB), "r"(scaleD));
}

__device__ __forceinline__ void wgmma_n40_rs_k(float (&d)[20], uint32_t a0, uint32_t a1, uint32_t a2, uint32_t a3, uint64_t descB, int scaleD) {
  asm volatile(
    "{\n.reg .pred p;\nsetp.ne.b32 p, %25, 0;\n"
    "wgmma.mma_async.sync.aligned.m64n40k16.f32.bf16.bf16 "
    "{%0, %1, %2, %3, %4, %5, %6, %7, %8, %9, %10, %11, %12, %13, %14, %15, "
    "%16, %17, %18, %19}, "
    "{%20, %21, %22, %23}, %24, p, 1, 1, 0;\n}\n"
    : "+f"(d[0]), "+f"(d[1]), "+f"(d[2]), "+f"(d[3]), "+f"(d[4]), "+f"(d[5]), "+f"(d[6]), "+f"(d[7]),
      "+f"(d[8]), "+f"(d[9]), "+f"(d[10]), "+f"(d[11]), "+f"(d[12]), "+f"(d[13]), "+f"(d[14]), "+f"(d[15]),
      "+f"(d[16]), "+f"(d[17]), "+f"(d[18]), "+f"(d[19])
    : "r"(a0), "r"(a1), "r"(a2), "r"(a3), "l"(descB), "r"(scaleD));
}

__device__ __forceinline__ void wgmma_n256_kk_first(float (&d)[128], uint64_t descA, uint64_t descB) {
  asm volatile(
    "{\n.reg .pred p;\nsetp.ne.b32 p, 0, 0;\n"
    "wgmma.mma_async.sync.aligned.m64n256k16.f32.bf16.bf16 "
    "{%0, %1, %2, %3, %4, %5, %6, %7, %8, %9, %10, %11, %12, %13, %14, %15, "
    "%16, %17, %18, %19, %20, %21, %22, %23, %24, %25, %26, %27, %28, %29, %30, %31, "
    "%32, %33, %34, %35, %36, %37, %38, %39, %40, %41, %42, %43, %44, %45, %46, %47, "
    "%48, %49, %50, %51, %52, %53, %54, %55, %56, %57, %58, %59, %60, %61, %62, %63, "
    "%64, %65, %66, %67, %68, %69, %70, %71, %72, %73, %74, %75, %76, %77, %78, %79, "
    "%80, %81, %82, %83, %84, %85, %86, %87, %88, %89, %90, %91, %92, %93, %94, %95, "
    "%96, %97, %98, %99, %100, %101, %102, %103, %104, %105, %106, %107, %108, %109, %110, %111, "
    "%112, %113, %114, %115, %116, %117, %118, %119, %120, %121, %122, %123, %124, %125, %126, %127}, "
    "%128, %129, p, 1, 1, 0, 0;\n}\n"
    : "=f"(d[0]), "=f"(d[1]), "=f"(d[2]), "=f"(d[3]), "=f"(d[4]), "=f"(d[5]), "=f"(d[6]), "=f"(d[7]),
      "=f"(d[8]), "=f"(d[9]), "=f"(d[10]), "=f"(d[11]), "=f"(d[12]), "=f"(d[13]), "=f"(d[14]), "=f"(d[15]),
      "=f"(d[16]), "=f"(d[17]), "=f"(d[18]), "=f"(d[19]), "=f"(d[20]), "=f"(d[21]), "=f"(d[22]), "=f"(d[23]),
      "=f"(d[24]), "=f"(d[25]), "=f"(d[26]), "=f"(d[27]), "=f"(d[28]), "=f"(d[29]), "=f"(d[30]), "=f"(d[31]),
      "=f"(d[32]), "=f"(d[33]), "=f"(d[34]), "=f"(d[35]), "=f"(d[36]), "=f"(d[37]), "=f"(d[38]), "=f"(d[39]),
      "=f"(d[40]), "=f"(d[41]), "=f"(d[42]), "=f"(d[43]), "=f"(d[44]), "=f"(d[45]), "=f"(d[46]), "=f"(d[47]),
      "=f"(d[48]), "=f"(d[49]), "=f"(d[50]), "=f"(d[51]), "=f"(d[52]), "=f"(d[53]), "=f"(d[54]), "=f"(d[55]),
      "=f"(d[56]), "=f"(d[57]), "=f"(d[58]), "=f"(d[59]), "=f"(d[60]), "=f"(d[61]), "=f"(d[62]), "=f"(d[63]),
      "=f"(d[64]), "=f"(d[65]), "=f"(d[66]), "=f"(d[67]), "=f"(d[68]), "=f"(d[69]), "=f"(d[70]), "=f"(d[71]),
      "=f"(d[72]), "=f"(d[73]), "=f"(d[74]), "=f"(d[75]), "=f"(d[76]), "=f"(d[77]), "=f"(d[78]), "=f"(d[79]),
      "=f"(d[80]), "=f"(d[81]), "=f"(d[82]), "=f"(d[83]), "=f"(d[84]), "=f"(d[85]), "=f"(d[86]), "=f"(d[87]),
      "=f"(d[88]), "=f"(d[89]), "=f"(d[90]), "=f"(d[91]), "=f"(d[92]), "=f"(d[93]), "=f"(d[94]), "=f"(d[95]),
      "=f"(d[96]), "=f"(d[97]), "=f"(d[98]), "=f"(d[99]), "=f"(d[100]), "=f"(d[101]), "=f"(d[102]), "=f"(d[103]),
      "=f"(d[104]), "=f"(d[105]), "=f"(d[106]), "=f"(d[107]), "=f"(d[108]), "=f"(d[109]), "=f"(d[110]), "=f"(d[111]),
      "=f"(d[112]), "=f"(d[113]), "=f"(d[114]), "=f"(d[115]), "=f"(d[116]), "=f"(d[117]), "=f"(d[118]), "=f"(d[119]),
      "=f"(d[120]), "=f"(d[121]), "=f"(d[122]), "=f"(d[123]), "=f"(d[124]), "=f"(d[125]), "=f"(d[126]), "=f"(d[127])
    : "l"(descA), "l"(descB));
}

__device__ __forceinline__ void wgmma_n256_kn_first(float (&d)[128], uint64_t descA, uint64_t descB) {
  asm volatile(
    "{\n.reg .pred p;\nsetp.ne.b32 p, 0, 0;\n"
    "wgmma.mma_async.sync.aligned.m64n256k16.f32.bf16.bf16 "
    "{%0, %1, %2, %3, %4, %5, %6, %7, %8, %9, %10, %11, %12, %13, %14, %15, "
    "%16, %17, %18, %19, %20, %21, %22, %23, %24, %25, %26, %27, %28, %29, %30, %31, "
    "%32, %33, %34, %35, %36, %37, %38, %39, %40, %41, %42, %43, %44, %45, %46, %47, "
    "%48, %49, %50, %51, %52, %53, %54, %55, %56, %57, %58, %59, %60, %61, %62, %63, "
    "%64, %65, %66, %67, %68, %69, %70, %71, %72, %73, %74, %75, %76, %77, %78, %79, "
    "%80, %81, %82, %83, %84, %85, %86, %87, %88, %89, %90, %91, %92, %93, %94, %95, "
    "%96, %97, %98, %99, %100, %101, %102, %103, %104, %105, %106, %107, %108, %109, %110, %111, "
    "%112, %113, %114, %115, %116, %117, %118, %119, %120, %121, %122, %123, %124, %125, %126, %127}, "
    "%128, %129, p, 1, 1, 0, 1;\n}\n"
    : "=f"(d[0]), "=f"(d[1]), "=f"(d[2]), "=f"(d[3]), "=f"(d[4]), "=f"(d[5]), "=f"(d[6]), "=f"(d[7]),
      "=f"(d[8]), "=f"(d[9]), "=f"(d[10]), "=f"(d[11]), "=f"(d[12]), "=f"(d[13]), "=f"(d[14]), "=f"(d[15]),
      "=f"(d[16]), "=f"(d[17]), "=f"(d[18]), "=f"(d[19]), "=f"(d[20]), "=f"(d[21]), "=f"(d[22]), "=f"(d[23]),
      "=f"(d[24]), "=f"(d[25]), "=f"(d[26]), "=f"(d[27]), "=f"(d[28]), "=f"(d[29]), "=f"(d[30]), "=f"(d[31]),
      "=f"(d[32]), "=f"(d[33]), "=f"(d[34]), "=f"(d[35]), "=f"(d[36]), "=f"(d[37]), "=f"(d[38]), "=f"(d[39]),
      "=f"(d[40]), "=f"(d[41]), "=f"(d[42]), "=f"(d[43]), "=f"(d[44]), "=f"(d[45]), "=f"(d[46]), "=f"(d[47]),
      "=f"(d[48]), "=f"(d[49]), "=f"(d[50]), "=f"(d[51]), "=f"(d[52]), "=f"(d[53]), "=f"(d[54]), "=f"(d[55]),
      "=f"(d[56]), "=f"(d[57]), "=f"(d[58]), "=f"(d[59]), "=f"(d[60]), "=f"(d[61]), "=f"(d[62]), "=f"(d[63]),
      "=f"(d[64]), "=f"(d[65]), "=f"(d[66]), "=f"(d[67]), "=f"(d[68]), "=f"(d[69]), "=f"(d[70]), "=f"(d[71]),
      "=f"(d[72]), "=f"(d[73]), "=f"(d[74]), "=f"(d[75]), "=f"(d[76]), "=f"(d[77]), "=f"(d[78]), "=f"(d[79]),
      "=f"(d[80]), "=f"(d[81]), "=f"(d[82]), "=f"(d[83]), "=f"(d[84]), "=f"(d[85]), "=f"(d[86]), "=f"(d[87]),
      "=f"(d[88]), "=f"(d[89]), "=f"(d[90]), "=f"(d[91]), "=f"(d[92]), "=f"(d[93]), "=f"(d[94]), "=f"(d[95]),
      "=f"(d[96]), "=f"(d[97]), "=f"(d[98]), "=f"(d[99]), "=f"(d[100]), "=f"(d[101]), "=f"(d[102]), "=f"(d[103]),
      "=f"(d[104]), "=f"(d[105]), "=f"(d[106]), "=f"(d[107]), "=f"(d[108]), "=f"(d[109]), "=f"(d[110]), "=f"(d[111]),
      "=f"(d[112]), "=f"(d[113]), "=f"(d[114]), "=f"(d[115]), "=f"(d[116]), "=f"(d[117]), "=f"(d[118]), "=f"(d[119]),
      "=f"(d[120]), "=f"(d[121]), "=f"(d[122]), "=f"(d[123]), "=f"(d[124]), "=f"(d[125]), "=f"(d[126]), "=f"(d[127])
    : "l"(descA), "l"(descB));
}

__device__ __forceinline__ void wgmma_n256_mk_first(float (&d)[128], uint64_t descA, uint64_t descB) {
  asm volatile(
    "{\n.reg .pred p;\nsetp.ne.b32 p, 0, 0;\n"
    "wgmma.mma_async.sync.aligned.m64n256k16.f32.bf16.bf16 "
    "{%0, %1, %2, %3, %4, %5, %6, %7, %8, %9, %10, %11, %12, %13, %14, %15, "
    "%16, %17, %18, %19, %20, %21, %22, %23, %24, %25, %26, %27, %28, %29, %30, %31, "
    "%32, %33, %34, %35, %36, %37, %38, %39, %40, %41, %42, %43, %44, %45, %46, %47, "
    "%48, %49, %50, %51, %52, %53, %54, %55, %56, %57, %58, %59, %60, %61, %62, %63, "
    "%64, %65, %66, %67, %68, %69, %70, %71, %72, %73, %74, %75, %76, %77, %78, %79, "
    "%80, %81, %82, %83, %84, %85, %86, %87, %88, %89, %90, %91, %92, %93, %94, %95, "
    "%96, %97, %98, %99, %100, %101, %102, %103, %104, %105, %106, %107, %108, %109, %110, %111, "
    "%112, %113, %114, %115, %116, %117, %118, %119, %120, %121, %122, %123, %124, %125, %126, %127}, "
    "%128, %129, p, 1, 1, 1, 0;\n}\n"
    : "=f"(d[0]), "=f"(d[1]), "=f"(d[2]), "=f"(d[3]), "=f"(d[4]), "=f"(d[5]), "=f"(d[6]), "=f"(d[7]),
      "=f"(d[8]), "=f"(d[9]), "=f"(d[10]), "=f"(d[11]), "=f"(d[12]), "=f"(d[13]), "=f"(d[14]), "=f"(d[15]),
      "=f"(d[16]), "=f"(d[17]), "=f"(d[18]), "=f"(d[19]), "=f"(d[20]), "=f"(d[21]), "=f"(d[22]), "=f"(d[23]),
      "=f"(d[24]), "=f"(d[25]), "=f"(d[26]), "=f"(d[27]), "=f"(d[28]), "=f"(d[29]), "=f"(d[30]), "=f"(d[31]),
      "=f"(d[32]), "=f"(d[33]), "=f"(d[34]), "=f"(d[35]), "=f"(d[36]), "=f"(d[37]), "=f"(d[38]), "=f"(d[39]),
      "=f"(d[40]), "=f"(d[41]), "=f"(d[42]), "=f"(d[43]), "=f"(d[44]), "=f"(d[45]), "=f"(d[46]), "=f"(d[47]),
      "=f"(d[48]), "=f"(d[49]), "=f"(d[50]), "=f"(d[51]), "=f"(d[52]), "=f"(d[53]), "=f"(d[54]), "=f"(d[55]),
      "=f"(d[56]), "=f"(d[57]), "=f"(d[58]), "=f"(d[59]), "=f"(d[60]), "=f"(d[61]), "=f"(d[62]), "=f"(d[63]),
      "=f"(d[64]), "=f"(d[65]), "=f"(d[66]), "=f"(d[67]), "=f"(d[68]), "=f"(d[69]), "=f"(d[70]), "=f"(d[71]),
      "=f"(d[72]), "=f"(d[73]), "=f"(d[74]), "=f"(d[75]), "=f"(d[76]), "=f"(d[77]), "=f"(d[78]), "=f"(d[79]),
      "=f"(d[80]), "=f"(d[81]), "=f"(d[82]), "=f"(d[83]), "=f"(d[84]), "=f"(d[85]), "=f"(d[86]), "=f"(d[87]),
      "=f"(d[88]), "=f"(d[89]), "=f"(d[90]), "=f"(d[91]), "=f"(d[92]), "=f"(d[93]), "=f"(d[94]), "=f"(d[95]),
      "=f"(d[96]), "=f"(d[97]), "=f"(d[98]), "=f"(d[99]), "=f"(d[100]), "=f"(d[101]), "=f"(d[102]), "=f"(d[103]),
      "=f"(d[104]), "=f"(d[105]), "=f"(d[106]), "=f"(d[107]), "=f"(d[108]), "=f"(d[109]), "=f"(d[110]), "=f"(d[111]),
      "=f"(d[112]), "=f"(d[113]), "=f"(d[114]), "=f"(d[115]), "=f"(d[116]), "=f"(d[117]), "=f"(d[118]), "=f"(d[119]),
      "=f"(d[120]), "=f"(d[121]), "=f"(d[122]), "=f"(d[123]), "=f"(d[124]), "=f"(d[125]), "=f"(d[126]), "=f"(d[127])
    : "l"(descA), "l"(descB));
}

constexpr uint64_t DESC_K = desc_base(16, 1024, 1);
constexpr uint64_t DESC_MN = desc_base(8192, 1024, 1);
constexpr uint64_t DESC_N64 = desc_base(0, 512, 2);

enum : int { BAR_FULL = 0, BAR_EMPTY = 4, BAR_HST = 8, BAR_KVR = 9, BAR_BT = 10, BAR_WPHI = 13, BAR_X = 14, BAR_OST = 15, BAR_KVR1 = 11, BAR_BT2 = 20, BAR_ORD4 = 21, BAR_BTF = 25, BAR_CVT = 26, BAR_HRD = 28, BAR_CST = 29, BAR_BT1 = 30, BAR_FS = 32, NBAR = 36 };

struct Pipe { int stage; uint32_t phases; };
__device__ __forceinline__ uint32_t pipe_parity(const Pipe& p) { return (p.phases >> p.stage) & 1u; }
constexpr uint32_t RING4 = 0x0321, RING3 = 0x0021, RINGO = 0x2031;
__device__ __forceinline__ void pipe_next(Pipe& p, uint32_t table) {
  p.phases ^= 1u << p.stage;
  p.stage = (table >> (4 * p.stage)) & 3;
}
constexpr uint32_t OSTG = 0x3102;
__host__ __device__ constexpr int stage_of_kb(int kb) { return (OSTG >> (4 * kb)) & 3; }

template <int VAR, bool FIRST>
__device__ __forceinline__ void mma_kblock(float (&acc)[128], uint32_t sa, uint32_t sbb) {
  wgmma_fence();
#pragma unroll
  for (int k = 0; k < 4; k++) {
    const uint64_t da = make_desc(sa + k * (VAR == 2 ? 2048 : 32), VAR == 2 ? DESC_MN : DESC_K);
    const uint64_t db = make_desc(sbb + k * (VAR == 1 ? 2048 : 32), VAR == 1 ? DESC_MN : DESC_K);
    if (FIRST && k == 0) {
      if (VAR == 0) wgmma_n256_kk_first(acc, da, db);
      else if (VAR == 2) wgmma_n256_mk_first(acc, da, db);
      else wgmma_n256_kn_first(acc, da, db);
    } else {
      if (VAR == 0) wgmma_n256_kk(acc, da, db, 1);
      else if (VAR == 2) wgmma_n256_mk(acc, da, db, 1);
      else wgmma_n256_kn(acc, da, db, 1);
    }
  }
  wgmma_commit();
}
struct NoSlice { __device__ __forceinline__ void operator()(int) const {} };
template <int VAR, class Slice>
__device__ __forceinline__ void mma_tile(float (&acc)[128], int nkb, Pipe& p, uint32_t table, bool release_last, uint32_t sb, int wg, bool leader,
                                         Slice& slice, int tcb = 0) {
  const uint32_t bars = sb + SM_BAR;
  TK(tcb);
  mbar_wait(bars + (BAR_FULL + p.stage) * 8, pipe_parity(p));
  TK(tcb + 1);
  mma_kblock<VAR, true>(acc, sb + p.stage * STAGE_BYTES + wg * 8192, sb + p.stage * STAGE_BYTES + 16384);
  int prev = p.stage;
  pipe_next(p, table);
#pragma unroll 1
  for (int kb = 1; kb < nkb; kb++) {
    mbar_wait(bars + (BAR_FULL + p.stage) * 8, pipe_parity(p));
    if (kb < 16) TK(tcb + 1 + kb);
    mma_kblock<VAR, false>(acc, sb + p.stage * STAGE_BYTES + wg * 8192, sb + p.stage * STAGE_BYTES + 16384);
    wgmma_wait<1>();
    if (leader) mbar_arrive(bars + (BAR_EMPTY + prev) * 8);
    slice(kb);
    prev = p.stage;
    pipe_next(p, table);
  }
  wgmma_wait<0>();
  if (release_last && leader) mbar_arrive(bars + (BAR_EMPTY + prev) * 8);
  fence_regs(acc);
}

__device__ __forceinline__ void cmul(float& ar, float& ai, float br, float bi) {
  const float r = ar * br - ai * bi, i = ar * bi + ai * br;
  ar = r; ai = i;
}

struct ScanC { float lr, li, r1, r2, i1, i2; };

__device__ __forceinline__ ScanC scan_consts(int bmode, float Lre, float Lim, float log_dt) {
  const float dt = __bfloat162float(__float2bfloat16(expf(log_dt)));
  float sn, cs;
  sincosf(dt * Lim, &sn, &cs);
  const float mag = expf(dt * Lre);
  const float lr = mag * cs, li = mag * sn;
  const float inv = 1.0f / (Lre * Lre + Lim * Lim);
  const float cr = 2.0f * ((lr - 1.0f) * Lre + li * Lim) * inv, ci = 2.0f * (li * Lre - (lr - 1.0f) * Lim) * inv;
  ScanC c;
  c.lr = lr;
  if (bmode == 1) { c.li = -li; c.r1 = -ci; c.r2 = cr; c.i1 = -cr; c.i2 = -ci; }
  else { c.li = li; c.r1 = cr; c.r2 = -ci; c.i1 = -ci; c.i2 = -cr; }
  return c;
}

struct ScanSlices {
  ScanC C;
  float l64r, l64i, l128r, l128i, pr, pi, gr, gi;
  uint32_t bre, bim, sb, tag;
  const ulonglong2* agg;
  int tb, ph, lane, step;
  unsigned long long pw[4];

  __device__ __forceinline__ void begin(float (&acc)[128], int cb, int tb_, bool second, int wg, int w, uint32_t ep) {
    const int g = lane >> 2, q = lane & 3;
    const int cl = w * 8 + g;
    const float lr = C.lr, li = C.li;
    tb = tb_;
    float sr = 0.f, si = 0.f;
#pragma unroll
    for (int j = 0; j < 32; j++)
#pragma unroll
      for (int e = 0; e < 2; e++) {
        const float nr = fmaf(lr, sr, fmaf(-li, si, acc[4 * j + e]));
        const float ni = fmaf(lr, si, fmaf(li, sr, acc[4 * j + 2 + e]));
        sr = nr; si = ni;
      }
    l64r = lr; l64i = li;
#pragma unroll
    for (int i = 0; i < 6; i++) cmul(l64r, l64i, l64r, l64i);
    l128r = l64r; l128i = l64i;
    cmul(l128r, l128i, l128r, l128i);
    {
      float ur = __shfl_up_sync(0xffffffffu, sr, 1, 4), ui = __shfl_up_sync(0xffffffffu, si, 1, 4);
      if (q >= 1) { cmul(ur, ui, l64r, l64i); sr += ur; si += ui; }
      ur = __shfl_up_sync(0xffffffffu, sr, 2, 4); ui = __shfl_up_sync(0xffffffffu, si, 2, 4);
      if (q >= 2) { cmul(ur, ui, l128r, l128i); sr += ur; si += ui; }
    }
    tag = ep + 1;
    ulonglong2* ag = &g_agg[(cb * 8) * 64 + wg * 32 + cl];
    agg = ag;
    if (q == 3 && tb < 7) {
      const unsigned long long t64 = (unsigned long long)tag << 32;
      const unsigned long long w0 = t64 | __float_as_uint(sr), w1 = t64 | __float_as_uint(si);
      asm volatile("st.relaxed.gpu.global.v2.u64 [%0], {%1, %2};" :: "l"(ag + tb * 64), "l"(w0), "l"(w1) : "memory");
    }
    pr = __shfl_up_sync(0xffffffffu, sr, 1, 4); pi = __shfl_up_sync(0xffffffffu, si, 1, 4);
    if (q == 0) { pr = 0.f; pi = 0.f; }
    TS(threadIdx.x == 0, 13);
    if (second) mbar_wait(sb + SM_BAR + BAR_HRD * 8, 0);
    else bar_sync(1, 256);
    const uint32_t st3 = sb + 3 * STAGE_BYTES;
    const int rowi = cl * 4 + q;
    bim = st3 + wg * 16384 + rowi * 128;
    bre = (wg == 0 ? st3 + 32768 : sb + SM_SCR) + rowi * 128;
    ph = rowi & 7;
#pragma unroll
    for (int jc = 0; jc < 8; jc++) {
      const float* a = &acc[16 * jc];
      sts128(bre + ((jc ^ ph) << 4), make_uint4(pack_bf16(a[0], a[1]), pack_bf16(a[4], a[5]), pack_bf16(a[8], a[9]), pack_bf16(a[12], a[13])));
      sts128(bim + ((jc ^ ph) << 4), make_uint4(pack_bf16(a[2], a[3]), pack_bf16(a[6], a[7]), pack_bf16(a[10], a[11]), pack_bf16(a[14], a[15])));
    }
    TC(threadIdx.x == 0, 46);
    step = -1;
    pw[0] = pw[1] = pw[2] = pw[3] = 0ull;
    TC(threadIdx.x == 0, 47);
  }

  __device__ __forceinline__ void operator()(int kb) {
    if (step < 0) {
      const int q = lane & 3;
      float vr[2] = {0.f, 0.f}, vi[2] = {0.f, 0.f};
      uint32_t n = 0;
      while (true) {
        if (kb & 1) {
#pragma unroll
          for (int u = 0; u < 2; u++)
            if (q + 4 * u < tb)
              asm volatile("ld.relaxed.gpu.global.v2.u64 {%0, %1}, [%2];" : "=l"(pw[2 * u]), "=l"(pw[2 * u + 1]) : "l"(agg + (q + 4 * u) * 64) : "memory");
          if (kb < 7) return;
        }
        bool ok = true;
#pragma unroll
        for (int u = 0; u < 2; u++)
          if (q + 4 * u < tb) {
            ok = ok && (uint32_t)(pw[2 * u] >> 32) == tag && (uint32_t)(pw[2 * u + 1] >> 32) == tag;
            vr[u] = __uint_as_float((uint32_t)pw[2 * u]); vi[u] = __uint_as_float((uint32_t)pw[2 * u + 1]);
          }
        if (__all_sync(0xffffffffu, ok)) break;
        if (kb < 7) return;
        kb |= 1;
        if (++n > SPIN_LIMIT) __trap();
      }
      float hr = 0.f, hi = 0.f;
      float l256r = l128r, l256i = l128i;
      cmul(l256r, l256i, l256r, l256i);
      for (int j = 0; j < tb; j++) {
        const float tr = __shfl_sync(0xffffffffu, (j & 4) ? vr[1] : vr[0], (lane & ~3) + (j & 3));
        const float ti = __shfl_sync(0xffffffffu, (j & 4) ? vi[1] : vi[0], (lane & ~3) + (j & 3));
        cmul(hr, hi, l256r, l256i);
        hr += tr; hi += ti;
      }
      if (q & 1) cmul(hr, hi, l64r, l64i);
      if (q & 2) cmul(hr, hi, l128r, l128i);
      gr = hr + pr; gi = hi + pi;
      step = 0;
      TS(threadIdx.x == 0, 14);
    } else if (step < 8) {
      const int jc = step;
      const float lr = C.lr, li = C.li;
      const uint32_t ar = bre + ((jc ^ ph) << 4), ai = bim + ((jc ^ ph) << 4);
      const uint4 va = lds128(ar), vb = lds128(ai);
      const uint32_t wa[4] = {va.x, va.y, va.z, va.w}, wb[4] = {vb.x, vb.y, vb.z, vb.w};
      uint32_t orr[4], oi[4];
#pragma unroll
      for (int e2 = 0; e2 < 4; e2++) {
        float h_r[2], h_i[2];
#pragma unroll
        for (int e = 0; e < 2; e++) {
          const float ua = e ? bf_hi(wa[e2]) : bf_lo(wa[e2]), ub = e ? bf_hi(wb[e2]) : bf_lo(wb[e2]);
          const float nr = fmaf(lr, gr, fmaf(-li, gi, ua));
          const float ni = fmaf(lr, gi, fmaf(li, gr, ub));
          gr = nr; gi = ni;
          h_r[e] = fmaf(C.r1, gr, C.r2 * gi);
          h_i[e] = fmaf(C.i1, gr, C.i2 * gi);
        }
        orr[e2] = pack_bf16(h_r[0], h_r[1]);
        oi[e2] = pack_bf16(h_i[0], h_i[1]);
      }
      sts128(ar, make_uint4(orr[0], orr[1], orr[2], orr[3]));
      sts128(ai, make_uint4(oi[0], oi[1], oi[2], oi[3]));
      if (++step == 8) {
        fence_async_smem();
        __syncwarp();
        if (lane == 0) mbar_arrive(sb + SM_BAR + BAR_HST * 8);
        TS(threadIdx.x == 0, 2);
      }
    }
  }
};

__device__ __forceinline__ void quad_minmax(const uint32_t (&x)[8], uint32_t& mx, uint32_t& mn) {
  const uint32_t a = hmax2(hmax2(x[0], x[2]), hmax2(x[4], x[6])), bq = hmax2(hmax2(x[1], x[3]), hmax2(x[5], x[7]));
  const uint32_t c = hmin2(hmin2(x[0], x[2]), hmin2(x[4], x[6])), d = hmin2(hmin2(x[1], x[3]), hmin2(x[5], x[7]));
  mx = hmax2(__byte_perm(a, bq, 0x5410), __byte_perm(a, bq, 0x7632));
  mn = hmin2(__byte_perm(c, d, 0x5410), __byte_perm(c, d, 0x7632));
  mx = hmax2(mx, __shfl_xor_sync(0xffffffffu, mx, 1));
  mn = hmin2(mn, __shfl_xor_sync(0xffffffffu, mn, 1));
  mx = hmax2(mx, __shfl_xor_sync(0xffffffffu, mx, 2));
  mn = hmin2(mn, __shfl_xor_sync(0xffffffffu, mn, 2));
}
__device__ __forceinline__ float quad_sum(float v) {
  v += __shfl_xor_sync(0xffffffffu, v, 1);
  v += __shfl_xor_sync(0xffffffffu, v, 2);
  return v;
}

struct ExpOff { float p0, p1, m0, m1; };
__device__ __forceinline__ ExpOff dual_front(const uint32_t (&x)[8]) {
  uint32_t mx, mn;
  quad_minmax(x, mx, mn);
  return ExpOff{-LOG2E * bf_lo(mx), -LOG2E * bf_hi(mx), LOG2E * bf_lo(mn), LOG2E * bf_hi(mn)};
}
__device__ __forceinline__ void dual_exps(const uint32_t (&x)[8], const ExpOff& o, float (&ep)[16], float (&em)[16]) {
#pragma unroll
  for (int i = 0; i < 8; i++) {
    const float xl = bf_lo(x[i]), xh = bf_hi(x[i]);
    const float po = (i & 1) ? o.p1 : o.p0, mo = (i & 1) ? o.m1 : o.m0;
    ep[2 * i] = ex2(fmaf(xl, LOG2E, po));
    ep[2 * i + 1] = ex2(fmaf(xh, LOG2E, po));
    em[2 * i] = ex2(fmaf(xl, -LOG2E, mo));
    em[2 * i + 1] = ex2(fmaf(xh, -LOG2E, mo));
  }
}
__device__ __forceinline__ void norm_pack(const float (&e)[16], uint32_t (&out)[8]) {
  float s0 = (e[0] + e[1]) + (e[4] + e[5]) + ((e[8] + e[9]) + (e[12] + e[13]));
  float s1 = (e[2] + e[3]) + (e[6] + e[7]) + ((e[10] + e[11]) + (e[14] + e[15]));
  const float i0 = rcp(quad_sum(s0)), i1 = rcp(quad_sum(s1));
#pragma unroll
  for (int i = 0; i < 8; i++) {
    const float s = (i & 1) ? i1 : i0;
    out[i] = pack_bf16(e[2 * i] * s, e[2 * i + 1] * s);
  }
}

template <int J0, int NJ, int SUBSTRIDE>
__device__ __forceinline__ void dump_cols(const float (&acc)[128], uint32_t base, uint32_t rowoff, int cadd, int r8) {
#pragma unroll
  for (int j = 0; j < NJ; j += 2) {
    const float* a = &acc[4 * (J0 + j)];
    stsm4(base + (j >> 3) * SUBSTRIDE + rowoff + ((((j & 7) + cadd) ^ r8) << 4),
          pack_bf16(a[0], a[1]), pack_bf16(a[2], a[3]), pack_bf16(a[4], a[5]), pack_bf16(a[6], a[7]));
  }
}

__device__ __forceinline__ void kv_issue(float (&D0)[20], float (&D1)[20], int hh, uint32_t phib, uint32_t sb) {
  const uint32_t vb = sb + SM_SCR + hh * 8192;
#pragma unroll
  for (int i = 0; i < 20; i++) { D0[i] = 0.f; D1[i] = 0.f; }
  const uint64_t da = make_desc(phib, DESC_MN);
  const uint64_t db = make_desc(vb, DESC_N64) | ((uint64_t)((sb + SM_ONES - vb) >> 4) << 16);
  wgmma_fence();
#pragma unroll
  for (int ks = 0; ks < 8; ks += 2) {
    wgmma_n40_mn(D0, da + ks * 128, db + ks * 64 - ((uint64_t)(ks * 64) << 16), ks != 0);
    wgmma_n40_mn(D1, da + (ks + 1) * 128, db + (ks + 1) * 64 - ((uint64_t)((ks + 1) * 64) << 16), ks != 0);
  }
  wgmma_commit();
}
__device__ __forceinline__ void kv_finish(float (&D0)[20], float (&D1)[20], int hh, int wg, int w, int lane, uint32_t sb, int bar) {
  wgmma_wait<0>();
  fence_regs(D0); fence_regs(D1);
  bar_sync(2 + wg, 128);
  const int g = lane >> 2, q = lane & 3;
  const uint32_t kp = sb + SM_SCR + hh * 8192 + (q * 2) * 256 + (w * 16 + g) * 4;
#pragma unroll
  for (int j = 0; j < 4; j++) {
    sts32f(kp + j * 2048, D0[4 * j] + D1[4 * j]);
    sts32f(kp + j * 2048 + 256, D0[4 * j + 1] + D1[4 * j + 1]);
    sts32f(kp + j * 2048 + 32, D0[4 * j + 2] + D1[4 * j + 2]);
    sts32f(kp + j * 2048 + 256 + 32, D0[4 * j + 3] + D1[4 * j + 3]);
  }
  if (q == 0) {
    const uint32_t zp = sb + SM_ZT + hh * 256 + (w * 16 + g) * 4;
    asm volatile("st.shared.f32 [%0], %1;" :: "r"(zp), "f"(D0[16] + D1[16]) : "memory");
    asm volatile("st.shared.f32 [%0], %1;" :: "r"(zp + 32), "f"(D0[18] + D1[18]) : "memory");
  }
  __syncwarp();
  if (lane == 0) mbar_arrive(sb + SM_BAR + bar * 8);
}

__device__ __forceinline__ void q_finish(const float (&Dp)[20], const float (&Dm)[20], int lane, uint32_t a0, uint32_t a1) {
  float bp[2], bm[2];
#pragma unroll
  for (int rr = 0; rr < 2; rr++) {
    const float dp = Dp[16 + 2 * rr], sp = Dp[17 + 2 * rr], dm = Dm[16 + 2 * rr], sm = Dm[17 + 2 * rr];
    const float id = rcp(fmaf(dp, sm, fmaf(dm, sp, 1e-6f * sp * sm)));
    bp[rr] = __shfl_sync(0xffffffffu, sm * id, lane & ~3);
    bm[rr] = __shfl_sync(0xffffffffu, sp * id, lane & ~3);
  }
  uint32_t o[8];
#pragma unroll
  for (int i = 0; i < 8; i++)
    o[i] = pack_bf16(fmaf(Dp[2 * i], bp[i & 1], Dm[2 * i] * bm[i & 1]), fmaf(Dp[2 * i + 1], bp[i & 1], Dm[2 * i + 1] * bm[i & 1]));
  stsm4(a0, o[0], o[1], o[2], o[3]);
  stsm4(a1, o[4], o[5], o[6], o[7]);
}

__device__ __forceinline__ void phi_pair(const uint32_t (&xa)[8], const uint32_t (&xb)[8], uint32_t (&pp)[8], uint32_t (&pm)[8],
                                         uint32_t (&qp)[8], uint32_t (&qm)[8]) {
  const ExpOff oa = dual_front(xa), ob = dual_front(xb);
  float epa[16], ema[16], epb[16], emb[16];
  dual_exps(xa, oa, epa, ema);
  dual_exps(xb, ob, epb, emb);
  norm_pack(epa, pp); norm_pack(ema, pm); norm_pack(epb, qp); norm_pack(emb, qm);
}
__device__ __forceinline__ void phi_store(uint32_t dst, uint32_t c0, uint32_t c1, uint32_t c2, uint32_t c3, const uint32_t (&pp)[8],
                                          const uint32_t (&pm)[8]) {
  stsm4(dst + c0, pp[0], pp[1], pp[2], pp[3]); stsm4(dst + c1, pp[4], pp[5], pp[6], pp[7]);
  stsm4(dst + c2, pm[0], pm[1], pm[2], pm[3]); stsm4(dst + c3, pm[4], pm[5], pm[6], pm[7]);
}

__device__ __forceinline__ void epi_kv(float (&acc)[128], uint32_t par, int wg, int w, int lane, uint32_t sb, bool leader) {
  const int mat = lane >> 3, r8 = lane & 7, cadd = mat >> 1;
  const int row = wg * 64 + w * 16 + (mat & 1) * 8 + r8;
  const uint32_t rowoff = row * 128;
  const uint32_t st3 = sb + 3 * STAGE_BYTES, bars = sb + SM_BAR;
  const uint32_t c0 = ((0 + cadd) ^ r8) << 4, c1 = ((2 + cadd) ^ r8) << 4, c2 = ((4 + cadd) ^ r8) << 4, c3 = ((6 + cadd) ^ r8) << 4;
  TC(threadIdx.x == 0, 35);
  uint32_t ka[32], v3[8];
#pragma unroll
  for (int i = 0; i < 32; i++) ka[i] = pack_bf16(acc[2 * i], acc[2 * i + 1]);
#pragma unroll
  for (int i = 0; i < 8; i++) v3[i] = pack_bf16(acc[112 + 2 * i], acc[112 + 2 * i + 1]);
  mbar_wait(bars + BAR_WPHI * 8, par);
  const uint32_t vrow = sb + SM_SCR + row * 64;
  const int sw = (row >> 1) & 3;
#pragma unroll
  for (int j = 0; j < 12; j += 2) {
    const float* a = &acc[64 + 4 * j];
    stsm4(vrow + (j >> 2) * 8192 + ((((j & 3) + cadd) ^ sw) << 4),
          pack_bf16(a[0], a[1]), pack_bf16(a[2], a[3]), pack_bf16(a[4], a[5]), pack_bf16(a[6], a[7]));
  }
  uint32_t x0[8], x1[8], x2[8], x3[8];
  {
    float P0[16], P1[16], P2[16], P3[16];
#pragma unroll
    for (int i = 0; i < 16; i++) { P0[i] = 0.f; P1[i] = 0.f; P2[i] = 0.f; P3[i] = 0.f; }
    const uint64_t dw = make_desc(sb + SM_SCR + 24576, DESC_N64);
    wgmma_fence();
    wgmma_n32_rs_n(P0, ka[0], ka[1], ka[2], ka[3], dw, 0);
    wgmma_n32_rs_n(P1, ka[8], ka[9], ka[10], ka[11], dw + 128, 0);
    wgmma_n32_rs_n(P2, ka[16], ka[17], ka[18], ka[19], dw + 256, 0);
    wgmma_n32_rs_n(P3, ka[24], ka[25], ka[26], ka[27], dw + 384, 0);
    wgmma_n32_rs_n(P0, ka[4], ka[5], ka[6], ka[7], dw + 64, 1);
    wgmma_n32_rs_n(P1, ka[12], ka[13], ka[14], ka[15], dw + 192, 1);
    wgmma_n32_rs_n(P2, ka[20], ka[21], ka[22], ka[23], dw + 320, 1);
    wgmma_n32_rs_n(P3, ka[28], ka[29], ka[30], ka[31], dw + 448, 1);
    wgmma_commit();
    wgmma_wait<0>();
    fence_regs(P0); fence_regs(P1); fence_regs(P2); fence_regs(P3);
#pragma unroll
    for (int i = 0; i < 8; i++) {
      x0[i] = pack_bf16(P0[2 * i], P0[2 * i + 1]); x1[i] = pack_bf16(P1[2 * i], P1[2 * i + 1]);
      x2[i] = pack_bf16(P2[2 * i], P2[2 * i + 1]); x3[i] = pack_bf16(P3[2 * i], P3[2 * i + 1]);
    }
  }
  bar_sync(1, 256);
  stsm4(vrow + 3 * 8192 + (((0 + cadd) ^ sw) << 4), v3[0], v3[1], v3[2], v3[3]);
  stsm4(vrow + 3 * 8192 + (((2 + cadd) ^ sw) << 4), v3[4], v3[5], v3[6], v3[7]);
  TC(threadIdx.x == 0, 36);
  uint32_t pp[8], pm[8], qp[8], qm[8];
  phi_pair(x0, x1, pp, pm, qp, qm);
  phi_store(st3 + rowoff, c0, c1, c2, c3, pp, pm);
  phi_store(st3 + 16384 + rowoff, c0, c1, c2, c3, qp, qm);
  fence_async_smem();
  bar_sync(1, 256);
  float D0[20], D1[20];
  kv_issue(D0, D1, wg, st3 + wg * 16384, sb);
  TC(threadIdx.x == 0, 37);
  phi_pair(x2, x3, pp, pm, qp, qm);
  phi_store(st3 + 32768 + rowoff, c0, c1, c2, c3, pp, pm);
  kv_finish(D0, D1, wg, wg, w, lane, sb, BAR_KVR);
  bar_sync(1, 256);
  phi_store(st3 + rowoff, c0, c1, c2, c3, qp, qm);
  fence_async_smem();
  bar_sync(1, 256);
  TC(threadIdx.x == 0, 38);
  kv_issue(D0, D1, 2 + wg, st3 + (wg ? 0 : 32768), sb);
  kv_finish(D0, D1, 2 + wg, wg, w, lane, sb, BAR_KVR1);
  if (leader) mbar_arrive(bars + (BAR_EMPTY + 3) * 8);
}

__device__ __forceinline__ void epi_q(float (&acc)[128], int wg, int w, int lane, uint32_t sb, bool leader) {
  const int mat = lane >> 3, r8 = lane & 7, cadd = mat >> 1;
  const uint32_t rowoff = (wg * 64 + w * 16 + (mat & 1) * 8 + r8) * 128;
  const uint32_t bars = sb + SM_BAR;
  const uint32_t c0 = ((0 + cadd) ^ r8) << 4, c1 = ((2 + cadd) ^ r8) << 4, c2 = ((4 + cadd) ^ r8) << 4, c3 = ((6 + cadd) ^ r8) << 4;
  TC(threadIdx.x == 0, 0);
  uint32_t A[16];
  uint32_t x[8], x1[8];
  ExpOff o;
  {
    uint32_t qa[64];
#pragma unroll
    for (int i = 0; i < 64; i++) qa[i] = pack_bf16(acc[2 * i], acc[2 * i + 1]);
    mbar_wait(bars + BAR_WPHI * 8, 0);
    const uint64_t dw = make_desc(sb + 3 * STAGE_BYTES + 16384, DESC_N64);
    float P0[16], P1[16], P2[16], P3[16];
    auto project = [&](int hf) {
#pragma unroll
      for (int i = 0; i < 16; i++) { P0[i] = 0.f; P1[i] = 0.f; P2[i] = 0.f; P3[i] = 0.f; }
      const uint32_t* k = &qa[32 * hf];
      const uint64_t d = dw + hf * 512;
      wgmma_fence();
      wgmma_n32_rs_n(P0, k[0], k[1], k[2], k[3], d, 0);
      wgmma_n32_rs_n(P1, k[8], k[9], k[10], k[11], d + 128, 0);
      wgmma_n32_rs_n(P2, k[16], k[17], k[18], k[19], d + 256, 0);
      wgmma_n32_rs_n(P3, k[24], k[25], k[26], k[27], d + 384, 0);
      wgmma_n32_rs_n(P0, k[4], k[5], k[6], k[7], d + 64, 1);
      wgmma_n32_rs_n(P1, k[12], k[13], k[14], k[15], d + 192, 1);
      wgmma_n32_rs_n(P2, k[20], k[21], k[22], k[23], d + 320, 1);
      wgmma_n32_rs_n(P3, k[28], k[29], k[30], k[31], d + 448, 1);
      wgmma_commit();
    };
    auto put = [&](uint32_t dst, const float (&Pa)[16], const float (&Pb)[16]) {
      stsm4(dst + c0, pack_bf16(Pa[0], Pa[1]), pack_bf16(Pa[2], Pa[3]), pack_bf16(Pa[4], Pa[5]), pack_bf16(Pa[6], Pa[7]));
      stsm4(dst + c1, pack_bf16(Pa[8], Pa[9]), pack_bf16(Pa[10], Pa[11]), pack_bf16(Pa[12], Pa[13]), pack_bf16(Pa[14], Pa[15]));
      stsm4(dst + c2, pack_bf16(Pb[0], Pb[1]), pack_bf16(Pb[2], Pb[3]), pack_bf16(Pb[4], Pb[5]), pack_bf16(Pb[6], Pb[7]));
      stsm4(dst + c3, pack_bf16(Pb[8], Pb[9]), pack_bf16(Pb[10], Pb[11]), pack_bf16(Pb[12], Pb[13]), pack_bf16(Pb[14], Pb[15]));
    };
    project(0);
    wgmma_wait<0>();
    fence_regs(P0); fence_regs(P1); fence_regs(P2); fence_regs(P3);
#pragma unroll
    for (int i = 0; i < 8; i++) { x[i] = pack_bf16(P0[2 * i], P0[2 * i + 1]); x1[i] = pack_bf16(P1[2 * i], P1[2 * i + 1]); }
    put(sb + stage_of_kb(1) * STAGE_BYTES + rowoff, P2, P3);
    project(1);
    o = dual_front(x);
    float ep[16], em[16];
    dual_exps(x, o, ep, em);
    wgmma_wait<0>();
    fence_regs(P0); fence_regs(P1); fence_regs(P2); fence_regs(P3);
    put(sb + stage_of_kb(2) * STAGE_BYTES + rowoff, P0, P1);
    mbar_wait(bars + BAR_HRD * 8, 1);
    if (leader) mbar_arrive(bars + (BAR_EMPTY + 3) * 8);
    put(sb + stage_of_kb(3) * STAGE_BYTES + rowoff, P2, P3);
    __syncwarp();
#pragma unroll
    for (int i = 0; i < 8; i++) { A[i] = pack_bf16(ep[2 * i], ep[2 * i + 1]); A[8 + i] = pack_bf16(em[2 * i], em[2 * i + 1]); }
#pragma unroll
    for (int i = 0; i < 8; i++) x[i] = x1[i];
    o = dual_front(x);
  }
  mbar_wait(bars + BAR_BT * 8, 0);
  TC(threadIdx.x == 0, 1);
#pragma unroll 1
  for (int j = 0; j < 7; j++) {
    if (j == 4) mbar_wait(bars + BAR_BT1 * 8, 0);
    if (j == 6) mbar_wait(bars + BAR_BT2 * 8, 0);
    float Dp[20], Dm[20];
#pragma unroll
    for (int i = 0; i < 20; i++) { Dp[i] = 0.f; Dm[i] = 0.f; }
    const uint64_t db = make_desc(sb + SM_SCR + (j < 6 ? j : j - 6) * 5120, DESC_K);
    wgmma_fence();
    wgmma_n40_rs_k(Dp, A[0], A[1], A[2], A[3], db, 0);
    wgmma_n40_rs_k(Dm, A[8], A[9], A[10], A[11], db + 4, 0);
    wgmma_n40_rs_k(Dp, A[4], A[5], A[6], A[7], db + 2, 1);
    wgmma_n40_rs_k(Dm, A[12], A[13], A[14], A[15], db + 6, 1);
    wgmma_commit();
    const int jn = min(j + 2, 7);
    const uint32_t srcn = sb + ((OSTG >> (4 * (jn >> 1))) & 3) * STAGE_BYTES + rowoff;
    const int cn = (jn & 1) * 4 + cadd;
    uint32_t x2[8];
    ldsm4(srcn + ((cn ^ r8) << 4), x2[0], x2[1], x2[2], x2[3]);
    ldsm4(srcn + (((cn + 2) ^ r8) << 4), x2[4], x2[5], x2[6], x2[7]);
    float ep[16], em[16];
    dual_exps(x, o, ep, em);
    const ExpOff o2 = dual_front(x2);
    wgmma_wait<0>();
    fence_regs(Dp); fence_regs(Dm);
    if (j == 1) { __syncwarp(); if (lane == 0) mbar_arrive(bars + BAR_BTF * 8); }
    const uint32_t src = sb + ((OSTG >> (4 * (j >> 1))) & 3) * STAGE_BYTES + rowoff;
    const int c = (j & 1) * 4 + cadd;
    q_finish(Dp, Dm, lane, src + ((c ^ r8) << 4), src + (((c + 2) ^ r8) << 4));
#pragma unroll
    for (int i = 0; i < 8; i++) { A[i] = pack_bf16(ep[2 * i], ep[2 * i + 1]); A[8 + i] = pack_bf16(em[2 * i], em[2 * i + 1]); }
#pragma unroll
    for (int i = 0; i < 8; i++) x[i] = x2[i];
    o = o2;
    if (j & 1) {
      fence_async_smem();
      __syncwarp();
      if (lane == 0) mbar_arrive(bars + (BAR_OST + (j >> 1)) * 8);
      TC(threadIdx.x == 0, 2 + (j >> 1));
    }
  }
  {
    float Dp[20], Dm[20];
#pragma unroll
    for (int i = 0; i < 20; i++) { Dp[i] = 0.f; Dm[i] = 0.f; }
    const uint64_t db = make_desc(sb + SM_SCR + 5120, DESC_K);
    wgmma_fence();
    wgmma_n40_rs_k(Dp, A[0], A[1], A[2], A[3], db, 0);
    wgmma_n40_rs_k(Dm, A[8], A[9], A[10], A[11], db + 4, 0);
    wgmma_n40_rs_k(Dp, A[4], A[5], A[6], A[7], db + 2, 1);
    wgmma_n40_rs_k(Dm, A[12], A[13], A[14], A[15], db + 6, 1);
    wgmma_commit();
    wgmma_wait<0>();
    fence_regs(Dp); fence_regs(Dm);
    const uint32_t src = sb + stage_of_kb(3) * STAGE_BYTES + rowoff;
    q_finish(Dp, Dm, lane, src + c2, src + c3);
    fence_async_smem();
    __syncwarp();
    if (lane == 0) mbar_arrive(bars + (BAR_OST + 3) * 8);
    TC(threadIdx.x == 0, 5);
  }
  bar_sync(2 + wg, 128);
}

template <bool WITH_X>
__device__ __forceinline__ void final_store(float (&acc)[128], uint32_t sb, int wg, int w, int lane) {
  const int g = lane >> 2, q = lane & 3;
  const int r = w * 16 + g;
  const uint32_t bars = sb + SM_BAR;
  TC(threadIdx.x == 0, 40);
  if (WITH_X) mbar_wait(bars + BAR_X * 8, 0);
  bar_sync(1, 256);
  TC(threadIdx.x == 0, 41);
  const uint32_t lo = sb + 2 * STAGE_BYTES;
  const uint32_t toff = r * 128 + (q & 1) * 8;
  const int sw = r & 7, qh = q >> 1;
  const bool odd = g & 1;
  const uint32_t o1 = odd ? 4 : 0, o2 = odd ? 0 : 4;
  const uint32_t xrow = sb + (wg * 64 + r) * 128 + q * 4, drow = sb + SM_ZT + q * 4;
#pragma unroll
  for (int b2 = 0; b2 < 4; b2++) {
#pragma unroll
    for (int bb = 0; bb < 2; bb++) {
      const int b = b2 * 2 + bb, bi = wg * 8 + b;
      const uint32_t st = lo + bi * 8192 + toff;
#pragma unroll
      for (int j = 0; j < 4; j++) {
        const int jb = b * 4 + j;
        float v0 = acc[4 * jb], v1 = acc[4 * jb + 1], v2 = acc[4 * jb + 2], v3 = acc[4 * jb + 3];
        if (WITH_X) {
          const uint32_t xa = xrow + (jb >> 3) * 16384 + (((jb & 7) ^ sw) << 4);
          const uint32_t x0 = lds32(xa), x1 = lds32(xa + 1024), dd = lds32(drow + jb * 16);
          uint32_t p0, p1;
          asm("mul.rn.bf16x2 %0, %1, %2;" : "=r"(p0) : "r"(x0), "r"(dd));
          asm("mul.rn.bf16x2 %0, %1, %2;" : "=r"(p1) : "r"(x1), "r"(dd));
          v0 += bf_lo(p0); v1 += bf_hi(p0); v2 += bf_lo(p1); v3 += bf_hi(p1);
        }
        const uint32_t a = st + (((j * 2 + qh) ^ sw) << 4);
        sts32f(a + o1, odd ? v1 : v0); sts32f(a + o2, odd ? v0 : v1);
        sts32f(a + 1024 + o1, odd ? v3 : v2); sts32f(a + 1024 + o2, odd ? v2 : v3);
      }
    }
    fence_async_smem();
    __syncwarp();
    if (lane == 0) mbar_arrive(bars + (BAR_FS + b2) * 8);
  }
  TC(threadIdx.x == 0, 42);
  TC(threadIdx.x == 0, 43);
}

__device__ __forceinline__ void helper_setup(const Params& P, int b, int hw, int lane, uint32_t sb) {
  const int et = hw * 32 + lane;
  for (int i = et; i < 132; i += 96) {
    if (i < 128) reinterpret_cast<float4*>(g_kv)[b * 128 + i] = make_float4(0.f, 0.f, 0.f, 0.f);
    else reinterpret_cast<float4*>(g_z)[b * 4 + i - 128] = make_float4(0.f, 0.f, 0.f, 0.f);
  }
  if (et < 64) sts128(sb + SM_ONES + et * 16, make_uint4(0x3F803F80u, 0x3F803F80u, 0x3F803F80u, 0x3F803F80u));
  fence_async_smem();
  bar_sync(4, 96);
  if (et == 0) red_release_add(&g_cnt_zero, 1);
}

__device__ __forceinline__ void helper(const Params& P, int b, int hw, int lane, uint32_t sb, uint32_t ep) {
  const uint32_t bars = sb + SM_BAR;
  const bool mgr = hw == 0 && lane == 0;
  const int et = hw * 32 + lane;
  helper_setup(P, b, hw, lane, sb);
  TS(mgr, 11);
  if (b < 64) {
    const int rb = b & 15, oct = b >> 4;
    const uint32_t st3 = sb + 3 * STAGE_BYTES;
    {
#pragma unroll 1
      for (int i = et; i < 128; i += 96) {
        const int ch = (i >> 6) * 512 + (b & 7) * 64 + (i & 63);
        const ScanC c = scan_consts(P.bmode, __bfloat162float(P.lam_re[ch]), __bfloat162float(P.lam_im[ch]), __bfloat162float(P.log_dt[ch]));
        sts128(sb + SM_SCR + i * 32, make_uint4(__float_as_uint(c.lr), __float_as_uint(c.li), __float_as_uint(c.r1), __float_as_uint(c.r2)));
        sts128(sb + SM_SCR + i * 32 + 16, make_uint4(__float_as_uint(c.i1), __float_as_uint(c.i2), 0u, 0u));
      }
      bar_sync(4, 96);
      if (mgr) mbar_arrive(bars + BAR_CST * 8);
    }
#pragma unroll 1
    for (int t = 0; t < 2; t++) {
      if (!mgr) break;
      const int cb = t * 8 + (b & 7), tb = b >> 3;
      mbar_wait(bars + BAR_HST * 8, t);
      TC(true, 56);
#pragma unroll 1
      for (int i = 0; i < 8; i++) {
        const int reg = (0x2013 >> (4 * (i >> 1))) & 3;
        tma_store3(&P.mHTs, st3 + reg * 16384 + (i & 1) * 8192, 0, tb * 4,
                   cb * 128 + (reg == 0 ? 64 : reg == 1 ? 96 : reg == 2 ? 0 : 32) + (i & 1) * 16);
        bulk_commit();
        asm volatile("cp.async.bulk.wait_group.read 1;" ::: "memory");
        if (t == 1 && i == 2) {
          wait_counter(&g_kv_ready[2 * oct], ep + 1);
          fence_async_global();
          mbar_expect_tx(bars + BAR_BT * 8, 4 * 5120);
          bulk_load(sb + SM_SCR, g_kvb + oct * 8 * 320, 4 * 5120, bars + BAR_BT * 8);
        }
        if (t == 1 && i == 4) {
          mbar_expect_tx(bars + BAR_WPHI * 8, 16384);
          tma_load(st3 + 16384, &P.mWphi4, 0, oct * 256, bars + BAR_WPHI * 8);
          tma_load(st3 + 16384 + 8192, &P.mWphi4, 0, oct * 256 + 128, bars + BAR_WPHI * 8);
        }
      }
      bulk_wait_read();
      TC(true, 57);
      mbar_arrive(bars + BAR_HRD * 8);
      bulk_wait_all();
      red_release_add(&g_cnt_h[t * 8 + tb], 1);
      TC(true, 58);
      TS(true, t ? 16 : 15);
    }
    if (mgr) {
      wait_counter(&g_kv_ready[2 * oct + 1], ep + 1);
      fence_async_global();
      mbar_expect_tx(bars + BAR_BT1 * 8, 2 * 5120);
      bulk_load(sb + SM_SCR + 4 * 5120, g_kvb + (oct * 8 + 4) * 320, 2 * 5120, bars + BAR_BT1 * 8);
      TS(true, 18);
    }
#pragma unroll 1
    for (int kb = 0; kb < 4; kb++) {
      if (kb == 0 && mgr) {
        mbar_wait(bars + BAR_BTF * 8, 0);
        mbar_expect_tx(bars + BAR_BT2 * 8, 2 * 5120);
        bulk_load(sb + SM_SCR, g_kvb + (oct * 8 + 6) * 320, 2 * 5120, bars + BAR_BT2 * 8);
      }
      if (!mgr) break;
      mbar_wait(bars + (BAR_OST + kb) * 8, 0);
      if (mgr) {
        const uint32_t src = sb + stage_of_kb(kb) * STAGE_BYTES;
        tma_store(&P.mO64, src, oct * 256 + kb * 64, rb * 128);
        bulk_commit();
        bulk_wait_read();
        tma_store(&P.mO64, src + 8192, oct * 256 + kb * 64, rb * 128 + 64);
        bulk_commit();
        bulk_wait_read();
        mbar_arrive(bars + (BAR_ORD4 + kb) * 8);
        bulk_wait_all();
        red_release_add(&g_cnt_o[rb * 4 + oct], 1);
      }
    }
    TS(mgr, 24);
  } else {
    uint32_t cvt_par = 0;
    if (mgr) wait_counter(&g_cnt_zero, (ep + 1) * NCTA);
    bar_sync(4, 96);
#pragma unroll 1
    for (int t = 0; t < 2; t++) {
      const int hq = 2 * ((b - 64) >> 4) + t;
      if (mgr) {
        fence_async_smem();
        mbar_expect_tx(bars + BAR_WPHI * 8, 8192);
        tma_load(sb + SM_SCR + 24576, &P.mWphi4, 0, hq * 128, bars + BAR_WPHI * 8);
      }
#pragma unroll 1
      for (int pr = 0; pr < 2; pr++) {
        mbar_wait(bars + (pr ? BAR_KVR1 : BAR_KVR) * 8, t);
        TC(mgr && pr == 1, 54);
#pragma unroll 2
        for (int i = et; i < 1024 + 32; i += 96) {
          const uint4 v = lds128(i < 1024 ? sb + SM_SCR + pr * 16384 + i * 16 : sb + SM_ZT + pr * 512 + (i - 1024) * 16);
          float* dst = i < 1024 ? g_kv + hq * 8192 + pr * 4096 + i * 4 : g_z + hq * 256 + pr * 128 + (i - 1024) * 4;
          asm volatile("red.global.add.v4.f32 [%0], {%1, %2, %3, %4};" :: "l"(dst), "f"(__uint_as_float(v.x)), "f"(__uint_as_float(v.y)),
                       "f"(__uint_as_float(v.z)), "f"(__uint_as_float(v.w)) : "memory");
        }
      }
      bar_sync(4, 96);
      if (mgr) {
        const uint32_t old = atom_add_acq_rel(&g_cnt_kv[hq], 1);
        asm volatile("st.shared.u32 [%0], %1;" :: "r"(bars + 248), "r"(old == ep * 16 + 15 ? 1u : 0u) : "memory");
      }
      TC(mgr, 55);
      TS(mgr, t ? 17 : 20);
      bar_sync(4, 96);
      if (lds32(bars + 248)) {
        TC(mgr, 59);
        if (mgr) {
          fence_async_global();
          fence_async_smem();
          mbar_expect_tx(bars + BAR_CVT * 8, 32768 + 1024);
          bulk_load(sb + SM_SCR, g_kv + hq * 8192, 32768, bars + BAR_CVT * 8);
          bulk_load(sb + SM_ZT, g_z + hq * 256, 1024, bars + BAR_CVT * 8);
        }
        mbar_wait(bars + BAR_CVT * 8, cvt_par);
        cvt_par ^= 1;
#pragma unroll 2
        for (int item = et; item < 1024; item += 96) {
          const int fc = item & 7, d = (item >> 3) & 31, hh = item >> 8;
          const uint4 a0 = lds128(sb + SM_SCR + item * 32), a1 = lds128(sb + SM_SCR + item * 32 + 16);
          g_kvb[(hq * 4 + hh) * 320 + d * 8 + (fc ^ (d & 7))] =
              make_uint4(pack_bf16(__uint_as_float(a0.x), __uint_as_float(a0.y)), pack_bf16(__uint_as_float(a0.z), __uint_as_float(a0.w)),
                         pack_bf16(__uint_as_float(a1.x), __uint_as_float(a1.y)), pack_bf16(__uint_as_float(a1.z), __uint_as_float(a1.w)));
        }
        for (int i = et; i < 256; i += 96) {
          const int hh = i >> 6, row = 32 + ((i >> 3) & 7), fc = i & 7;
          uint4 v = make_uint4(0u, 0u, 0u, 0u);
          if (row == 32) {
            const uint4 a0 = lds128(sb + SM_ZT + hh * 256 + fc * 32), a1 = lds128(sb + SM_ZT + hh * 256 + fc * 32 + 16);
            v = make_uint4(pack_bf16(__uint_as_float(a0.x), __uint_as_float(a0.y)), pack_bf16(__uint_as_float(a0.z), __uint_as_float(a0.w)),
                           pack_bf16(__uint_as_float(a1.x), __uint_as_float(a1.y)), pack_bf16(__uint_as_float(a1.z), __uint_as_float(a1.w)));
          } else if (row == 33) v = make_uint4(0x3F803F80u, 0x3F803F80u, 0x3F803F80u, 0x3F803F80u);
          g_kvb[(hq * 4 + hh) * 320 + row * 8 + (fc ^ (row & 7))] = v;
        }
        fence_async_global();
        bar_sync(4, 96);
        TC(mgr, 60);
        if (mgr) st_release(&g_kv_ready[hq], ep + 1);
        TC(mgr, 61);
      }
      bar_sync(4, 96);
    }
    if (mgr) mbar_arrive(bars + BAR_HRD * 8);
  }
}

__device__ __forceinline__ uint32_t prod_acquire(Pipe& p, uint32_t sb, uint32_t bytes) {
  const uint32_t bars = sb + SM_BAR;
  mbar_wait(bars + (BAR_EMPTY + p.stage) * 8, pipe_parity(p) ^ 1);
  mbar_expect_tx(bars + (BAR_FULL + p.stage) * 8, bytes);
  return sb + p.stage * STAGE_BYTES;
}

__device__ __forceinline__ void producer(const Params& P, int b, uint32_t sb, uint32_t ep) {
  const uint32_t bars = sb + SM_BAR;
  Pipe p{0, 0};
  TC(true, 48);
  TS(true, 19);
  const int out_row = (b & 15) * 128, out_col = b < 64 ? (b >> 4) * 256 : 1024 + ((b - 64) >> 4) * 256;
  if (b < 64) {
    const int tb = b >> 3, rb = b & 15, oct = b >> 4;
#pragma unroll 1
    for (int i = 0; i < 32; i++) {
      const int kb = i & 15, cb = (i >> 4) * 8 + (b & 7);
      const uint32_t st = prod_acquire(p, sb, STAGE_BYTES), fb = bars + (BAR_FULL + p.stage) * 8;
      if (P.bmode < 2) tma_load4(st, &P.mBri, kb * 64, 0, 0, cb * 8, fb);
      else {
        for (int gq = 0; gq < 8; gq++) {
          tma_load(st + gq * 2048, &P.mBre, kb * 64, cb * 64 + gq * 8, fb);
          tma_load(st + gq * 2048 + 1024, &P.mBim, kb * 64, cb * 64 + gq * 8, fb);
        }
      }
      tma_load4(st + 16384, &P.mBx, kb * 64, 0, tb * 4, 0, fb);
      if (i < 16) pipe_next(p, RING4); else pipe_next(p, RING3);
    }
    for (int kb = 0; kb < 16; kb++) {
      const uint32_t st = prod_acquire(p, sb, STAGE_BYTES), fb = bars + (BAR_FULL + p.stage) * 8;
      tma_load(st, &P.mAx, kb * 64, rb * 128, fb);
#pragma unroll
      for (int j = 0; j < 4; j++) tma_load(st + 16384 + j * 8192, &P.mWv, oct * 256 + j * 64, kb * 64, fb);
      pipe_next(p, RING3);
    }
    for (int i = 0; i < 16; i++) {
      int koff;
      const bool own = i < 4;
      if (own) koff = oct * 256 + i * 64;
      else {
        const int r = i - 4, kb = r / 3, o2 = (oct + 1 + r % 3) & 3;
        koff = o2 * 256 + kb * 64;
        if (i < 8) mbar_wait(bars + (BAR_ORD4 + i - 4) * 8, 0);
        wait_counter(&g_cnt_o[rb * 4 + o2], ep * 4 + kb + 1);
        fence_async_global();
      }
      const uint32_t st = prod_acquire(p, sb, own ? 32768 : STAGE_BYTES), fb = bars + (BAR_FULL + p.stage) * 8;
      if (!own) tma_load(st, &P.mO, koff, rb * 128, fb);
#pragma unroll
      for (int j = 0; j < 4; j++) tma_load(st + 16384 + j * 8192, &P.mWo, oct * 256 + j * 64, koff, fb);
      pipe_next(p, RINGO);
    }
  } else {
    const int rb = b & 15, hi = (b - 64) >> 4;
#pragma unroll 1
    for (int i = 0; i < 32; i++) {
      const int kb = i & 15, hq = 2 * hi + (i >> 4);
      const uint32_t st = prod_acquire(p, sb, STAGE_BYTES), fb = bars + (BAR_FULL + p.stage) * 8;
      tma_load(st, &P.mAx, kb * 64, rb * 128, fb);
      tma_load(st + 16384, &P.mWv, 1024 + hq * 128, kb * 64, fb);
      tma_load(st + 24576, &P.mWv, 1024 + hq * 128 + 64, kb * 64, fb);
      tma_load(st + 32768, &P.mWv, 2048 + hq * 128, kb * 64, fb);
      tma_load(st + 40960, &P.mWv, 2048 + hq * 128 + 64, kb * 64, fb);
      pipe_next(p, RING4);
    }
    for (int i = 0; i < 32; i++) {
      if ((i & 15) == 0) {
        TS(true, 28);
        wait_counter(&g_cnt_h[(i >> 4) * 8 + (rb >> 1)], (ep + 1) * 8);
        TS(true, 29);
        fence_async_global();
      }
      const uint32_t st = prod_acquire(p, sb, STAGE_BYTES), fb = bars + (BAR_FULL + p.stage) * 8;
      tma_load(st, &P.mHT, rb * 128, i * 64, fb);
      tma_load(st + 8192, &P.mHT, rb * 128 + 64, i * 64, fb);
      tma_load(st + 16384, (i & 1) ? &P.mCim : &P.mCre, (i >> 1) * 64, hi * 256, fb);
      pipe_next(p, RING4);
    }
    mbar_wait(bars + (BAR_EMPTY + 0) * 8, ((p.phases >> 0) & 1) ^ 1);
    mbar_wait(bars + (BAR_EMPTY + 1) * 8, ((p.phases >> 1) & 1) ^ 1);
    mbar_wait(bars + BAR_HRD * 8, 0);
    mbar_expect_tx(bars + BAR_X * 8, 65536 + 512);
    bulk_load(sb + SM_ZT, P.dskip + hi * 256, 512, bars + BAR_X * 8);
#pragma unroll
    for (int j = 0; j < 4; j++) tma_load(sb + j * 16384, &P.mBxT, hi * 256 + j * 64, rb * 128, bars + BAR_X * 8);
  }
#pragma unroll 1
  for (int g2 = 0; g2 < 4; g2++) {
    mbar_wait(bars + (BAR_FS + g2) * 8, 0);
#pragma unroll
    for (int u = 0; u < 4; u++) {
      const int wg = u >> 1, bx = g2 * 2 + (u & 1);
      tma_store(&P.mOut, sb + 2 * STAGE_BYTES + (wg * 8 + bx) * 8192, out_col + bx * 32, out_row + wg * 64);
    }
    bulk_commit();
  }
  bulk_wait_all();
  TS(true, 8);
  g_epoch[b] = ep + 1;
}

__global__ void __launch_bounds__(NTHREADS, 1) fused_kernel(const __grid_constant__ Params P) {
  extern __shared__ __align__(1024) uint8_t smem_raw[];
  const uint32_t sb = smem_u32(smem_raw);
  const int b = blockIdx.x, warp = threadIdx.x >> 5, lane = threadIdx.x & 31;
  const uint32_t bars = sb + SM_BAR;
  TS(threadIdx.x == 0, 9);
  TC(threadIdx.x == 256, 44);
  if (threadIdx.x == 256) {
    if (sb & 1023) __trap();
    for (int s = 0; s < STAGES; s++) { mbar_init(bars + (BAR_FULL + s) * 8, 1); mbar_init(bars + (BAR_EMPTY + s) * 8, 2); }
    mbar_init(bars + BAR_HST * 8, 8);
    mbar_init(bars + BAR_KVR * 8, 8);
    mbar_init(bars + BAR_BT * 8, 1);
    mbar_init(bars + BAR_KVR1 * 8, 8);
    mbar_init(bars + BAR_BT2 * 8, 1);
    mbar_init(bars + BAR_BTF * 8, 8);
    mbar_init(bars + BAR_CVT * 8, 1);
    mbar_init(bars + BAR_HRD * 8, 1);
    mbar_init(bars + BAR_CST * 8, 1);
    mbar_init(bars + BAR_BT1 * 8, 1);
    for (int i = 0; i < 4; i++) mbar_init(bars + (BAR_FS + i) * 8, 8);
    for (int i = 0; i < 4; i++) mbar_init(bars + (BAR_ORD4 + i) * 8, 1);
    for (int i = 0; i < 4; i++) mbar_init(bars + (BAR_OST + i) * 8, 8);
    mbar_init(bars + BAR_WPHI * 8, 1);
    mbar_init(bars + BAR_X * 8, 1);
    asm volatile("fence.mbarrier_init.release.cluster;" ::: "memory");
    TC(true, 45);
    prefetch_map(&P.mBri); prefetch_map(&P.mBx);
    TC(true, 46);
  }
  __syncthreads();
  TC(threadIdx.x == 256, 47);
  uint32_t ep;
  asm volatile("ld.relaxed.gpu.global.u32 %0, [%1];" : "=r"(ep) : "l"(&g_epoch[b]) : "memory");

  if (warp < 8) {
    reg_alloc<REG_MMA>();
    const int wg = warp >> 2, w = warp & 3;
    const bool leader = (threadIdx.x & 127) == 0;
    float acc[128];
    Pipe p{0, 0};
    NoSlice none;
    TS(threadIdx.x == 0, 0);
    if (b < 64) {
      const int tb = b >> 3;
      ScanSlices scan;
      scan.sb = sb; scan.lane = lane; scan.step = 8; scan.tb = 0; scan.tag = 0;
      ScanC C1;
      int t = 0;
#pragma unroll 1
      while (true) {
        mma_tile<0>(acc, 16, p, t ? RING3 : RING4, t == 1, sb, wg, leader, scan, t * 20);
        TS(threadIdx.x == 0, t ? 3 : 1);
        if (t == 0) {
          mbar_wait(bars + BAR_CST * 8, 0);
          const uint32_t ca = sb + SM_SCR + (warp * 8 + (lane >> 2)) * 32;
          const uint4 u0 = lds128(ca), u1 = lds128(ca + 16), v0 = lds128(ca + 2048), v1 = lds128(ca + 2048 + 16);
          scan.C = ScanC{__uint_as_float(u0.x), __uint_as_float(u0.y), __uint_as_float(u0.z), __uint_as_float(u0.w), __uint_as_float(u1.x),
                         __uint_as_float(u1.y)};
          C1 = ScanC{__uint_as_float(v0.x), __uint_as_float(v0.y), __uint_as_float(v0.z), __uint_as_float(v0.w), __uint_as_float(v1.x),
                     __uint_as_float(v1.y)};
        } else scan.C = C1;
        scan.begin(acc, t * 8 + (b & 7), tb, t == 1, wg, w, ep);
        TS(threadIdx.x == 0, t ? 4 : 12);
        if (++t == 2) break;
      }
      mma_tile<1>(acc, 16, p, RING3, true, sb, wg, leader, scan, 40);
      TS(threadIdx.x == 0, 5);
      epi_q(acc, wg, w, lane, sb, leader);
      TS(threadIdx.x == 0, 6);
      mma_tile<1>(acc, 16, p, RINGO, true, sb, wg, leader, none, 60);
      TS(threadIdx.x == 0, 7);
      final_store<false>(acc, sb, wg, w, lane);
    } else {
      int t = 0;
#pragma unroll 1
      while (true) {
        mma_tile<1>(acc, 16, p, RING4, false, sb, wg, leader, none, t * 20);
        TS(threadIdx.x == 0, t ? 3 : 1);
        epi_kv(acc, t, wg, w, lane, sb, leader);
        TS(threadIdx.x == 0, t ? 4 : 12);
        if (++t == 2) break;
      }
      mma_tile<2>(acc, 32, p, RING4, true, sb, wg, leader, none, 40);
      TS(threadIdx.x == 0, 7);
      final_store<true>(acc, sb, wg, w, lane);
    }
  } else {
    reg_dealloc<REG_AUX>();
    if (warp == 8) { if (lane == 0) producer(P, b, sb, ep); }
    else helper(P, b, warp - 9, lane, sb, ep);
  }
}

typedef CUresult (*EncodeTiledFn)(CUtensorMap*, CUtensorMapDataType, cuuint32_t, void*, const cuuint64_t*, const cuuint64_t*,
                                  const cuuint32_t*, const cuuint32_t*, CUtensorMapInterleave, CUtensorMapSwizzle,
                                  CUtensorMapL2promotion, CUtensorMapFloatOOBfill);

CUresult make_map_nd(EncodeTiledFn fn, CUtensorMap* m, const void* ptr, bool f32, int rank, const cuuint64_t* dims,
                     const cuuint64_t* strides, const cuuint32_t* box) {
  cuuint32_t es[5] = {1, 1, 1, 1, 1};
  return fn(m, f32 ? CU_TENSOR_MAP_DATA_TYPE_FLOAT32 : CU_TENSOR_MAP_DATA_TYPE_BFLOAT16, rank, const_cast<void*>(ptr), dims, strides, box,
            es, CU_TENSOR_MAP_INTERLEAVE_NONE, CU_TENSOR_MAP_SWIZZLE_128B, CU_TENSOR_MAP_L2_PROMOTION_L2_256B,
            CU_TENSOR_MAP_FLOAT_OOB_FILL_NONE);
}
void make_map(EncodeTiledFn fn, CUtensorMap* m, const void* ptr, bool f32, uint64_t inner, uint64_t outer, uint32_t box_inner,
              uint32_t box_outer) {
  cuuint64_t dims[2] = {inner, outer};
  cuuint64_t strides[1] = {inner * (f32 ? 4 : 2)};
  cuuint32_t box[2] = {box_inner, box_outer};
  make_map_nd(fn, m, ptr, f32, 2, dims, strides, box);
}

}

extern "C" void kernel_launch(void* const* d_in, const int* in_sizes, int n_in, void* d_out, int out_size) {
  (void)in_sizes; (void)n_in; (void)out_size;
  static Params P;
  static void* cached[14];
  static bool ready = false;
  bool same = ready;
  for (int i = 0; i < 13 && same; i++) same = cached[i] == d_in[i];
  same = same && cached[13] == d_out;
  if (!same) {
    void* fnp = nullptr;
    cudaDriverEntryPointQueryResult st;
    cudaGetDriverEntryPoint("cuTensorMapEncodeTiled", &fnp, cudaEnableDefault, &st);
    EncodeTiledFn fn = (EncodeTiledFn)fnp;
    void *pHT, *pO;
    cudaGetSymbolAddress(&pHT, g_hT);
    cudaGetSymbolAddress(&pO, g_o);
    {
      const uintptr_t re = (uintptr_t)d_in[7], im = (uintptr_t)d_in[8];
      const uint64_t diff = re < im ? im - re : re - im;
      P.bmode = 2;
      if (diff >= 1024ull * 1024 * 2 && diff < (1ull << 40) && (diff & 15) == 0) {
        cuuint64_t dims[4] = {1024, 8, 2, 128};
        cuuint64_t strides[3] = {2048, diff, 16384};
        cuuint32_t box[4] = {64, 8, 2, 8};
        if (make_map_nd(fn, &P.mBri, (void*)(re < im ? re : im), false, 4, dims, strides, box) == CUDA_SUCCESS) P.bmode = re < im ? 0 : 1;
      }
      if (P.bmode == 2) make_map(fn, &P.mBri, d_in[7], false, 1024, 1024, 64, 8);
    }
    make_map(fn, &P.mBre, d_in[7], false, 1024, 1024, 64, 8);
    make_map(fn, &P.mBim, d_in[8], false, 1024, 1024, 64, 8);
    {
      cuuint64_t dims[4] = {1024, 2, 32, 32};
      cuuint64_t strides[3] = {2048, 64 * 2048, 2 * 2048};
      cuuint32_t box[4] = {64, 2, 4, 32};
      make_map_nd(fn, &P.mBx, d_in[4], false, 4, dims, strides, box);
    }
    {
      cuuint64_t dims[3] = {64, 32, 2048};
      cuuint64_t strides[2] = {128, 4096};
      cuuint32_t box[3] = {64, 4, 16};
      make_map_nd(fn, &P.mHTs, pHT, false, 3, dims, strides, box);
    }
    {
      cuuint32_t es[2] = {1, 1};
      auto map64 = [&](CUtensorMap* m, void* ptr, cuuint64_t inner, cuuint64_t outer, cuuint32_t box_outer) {
        cuuint64_t dims[2] = {inner, outer};
        cuuint64_t strides[1] = {inner * 2};
        cuuint32_t box[2] = {32, box_outer};
        fn(m, CU_TENSOR_MAP_DATA_TYPE_BFLOAT16, 2, ptr, dims, strides, box, es, CU_TENSOR_MAP_INTERLEAVE_NONE, CU_TENSOR_MAP_SWIZZLE_64B,
           CU_TENSOR_MAP_L2_PROMOTION_NONE, CU_TENSOR_MAP_FLOAT_OOB_FILL_NONE);
      };
      map64(&P.mWphi4, d_in[2], 32, 1024, 128);
    }
    make_map(fn, &P.mAx, d_in[0], false, 1024, 2048, 64, 128);
    make_map(fn, &P.mBxT, d_in[4], false, 1024, 2048, 64, 128);
    make_map(fn, &P.mWv, d_in[1], false, 3072, 1024, 64, 64);
    make_map(fn, &P.mHT, pHT, false, 2048, 2048, 64, 64);
    make_map(fn, &P.mCre, d_in[9], false, 1024, 1024, 64, 256);
    make_map(fn, &P.mCim, d_in[10], false, 1024, 1024, 64, 256);
    make_map(fn, &P.mO, pO, false, 1024, 2048, 64, 128);
    make_map(fn, &P.mO64, pO, false, 1024, 2048, 64, 64);
    make_map(fn, &P.mWo, d_in[3], false, 1024, 1024, 64, 64);
    make_map(fn, &P.mOut, d_out, true, 2048, 2048, 32, 64);
    P.lam_re = (const __nv_bfloat16*)d_in[5];
    P.lam_im = (const __nv_bfloat16*)d_in[6];
    P.log_dt = (const __nv_bfloat16*)d_in[11];
    P.dskip = (const __nv_bfloat16*)d_in[12];
    cudaFuncSetAttribute(fused_kernel, cudaFuncAttributeMaxDynamicSharedMemorySize, SMEM_BYTES);
    for (int i = 0; i < 13; i++) cached[i] = d_in[i];
    cached[13] = d_out;
    ready = true;
  }
  fused_kernel<<<NCTA, NTHREADS, SMEM_BYTES>>>(P);
}
```
